```python
import torch

def _softmax(x, axis=-1):
    return torch.softmax(x, dim=axis)
def _gelu(x):
    return torch.nn.functional.gelu(x, approximate="tanh")
def _silu(x):
    return torch.nn.functional.silu(x)
def _sigmoid(x):
    return torch.sigmoid(x)
def _layernorm(x, axis=-1, eps=1e-5):
    m = x.mean(dim=axis, keepdim=True)
    v = x.var(dim=axis, keepdim=True, unbiased=False)
    return (x - m) / torch.sqrt(v + eps)
def _scatter_add(tgt, idx, src, axis=0):
    return tgt.clone().index_add_(axis, idx, src)
def _segment_sum(src, seg, n):
    out = torch.zeros((n,) + src.shape[1:], dtype=src.dtype)
    return out.index_add_(0, seg, src)
def _pad(x, pw):
    flat = tuple(v for pair in reversed(pw) for v in pair)
    return torch.nn.functional.pad(x, flat)

kernel_name = 'interleave_layers__mha_block_cached__dense_activation_gelu__decode'

def setup_inputs():

    _w = (lambda a: (lambda t: t.to(torch.bfloat16) if t.is_floating_point() else t)(torch.as_tensor(a)))
    def _A_setup():
        B, Sq, D = 2, 1, 512
        H, Sk, Dh = 32, 8192, 128
        return {
            "x": _w((lambda *s: torch.randn(*s, dtype=torch.bfloat16) * 0.1)(B, Sq, D)),
            "k_cache": _w((lambda *s: torch.randn(*s, dtype=torch.bfloat16) * 0.8)(B, H, Sk, Dh)),
            "v_cache": _w((lambda *s: torch.randn(*s, dtype=torch.bfloat16) * 3.2)(B, H, Sk, Dh)),
            "wq": _w((lambda *s: torch.randn(*s, dtype=torch.bfloat16) * 0.8)(D, H * Dh) * (D ** -0.5)),
            "wo": _w((lambda *s: torch.randn(*s, dtype=torch.bfloat16) * 3.2)(H * Dh, D) * ((H * Dh) ** -0.5)),
        }
    _A_in = _A_setup()

    def _B_setup():
        B, S, D, F = 2, 1, 512, 1792
        return {
            "x": _w((lambda *s: torch.randn(*s, dtype=torch.bfloat16) * 0.1)(B, S, D)),
            "w1": _w((lambda *s: torch.randn(*s, dtype=torch.bfloat16) * 1.6)(D, F) * (D ** -0.5)),
            "b1": _w((lambda *s: torch.randn(*s, dtype=torch.bfloat16) * 1.6)(F) * 0.01),
            "w2": _w((lambda *s: torch.randn(*s, dtype=torch.bfloat16) * 0.4)(F, D) * (F ** -0.5)),
            "b2": _w((lambda *s: torch.randn(*s, dtype=torch.bfloat16) * 0.4)(D) * 0.01),
        }
    _B_in = _B_setup()

    return {
        "A_x": _A_in["x"],
        "A_k_cache": _A_in["k_cache"],
        "A_v_cache": _A_in["v_cache"],
        "A_wq": _A_in["wq"],
        "A_wo": _A_in["wo"],
        "B_x": _B_in["x"],
        "B_w1": _B_in["w1"],
        "B_b1": _B_in["b1"],
        "B_w2": _B_in["w2"],
        "B_b2": _B_in["b2"],
    }

def reference(A_x, A_k_cache, A_v_cache, A_wq, A_wo, B_x, B_w1, B_b1, B_w2, B_b2):
    def _A_ref(x, k_cache, v_cache, wq, wo):
        B, Sq, D = x.shape
        H, Dh = 32, 128
        q = (lambda x, *d: x.permute(*d))((x @ wq).reshape(B, Sq, H, Dh), 0, 2, 1, 3)
        scores = torch.einsum("bhqd,bhkd->bhqk", q, k_cache) * (Dh ** -0.5)
        p = _softmax(scores, axis=-1)
        o = torch.einsum("bhqk,bhkd->bhqd", p, v_cache)
        return (lambda x, *d: x.permute(*d))(o, 0, 2, 1, 3).reshape(B, Sq, H * Dh) @ wo

    def _B_ref(x, w1, b1, w2, b2):
        h = torch.einsum("bsd,df->bsf", x, w1) + b1
        h = _gelu(h)
        return torch.einsum("bsf,fd->bsd", h, w2) + b2

    x = A_x
    x = x + _A_ref(_layernorm(x, axis=-1), A_k_cache, A_v_cache, A_wq, A_wo)
    x = x + _B_ref(_layernorm(x, axis=-1), B_w1, B_b1, B_w2, B_b2)
    x = x + _A_ref(_layernorm(x, axis=-1), A_k_cache, A_v_cache, A_wq, A_wo)
    x = x + _B_ref(_layernorm(x, axis=-1), B_w1, B_b1, B_w2, B_b2)
    return x
```

```cpp
#include <cuda_runtime.h>
#include <cuda.h>
#include <cuda_bf16.h>
#include <stdint.h>

namespace {

constexpr int NCTA = 128;
constexpr int DM = 512, FF = 1792, HD = 4096;
constexpr int NMLP = 112;
constexpr uint32_t HALF_B = 8192;
constexpr uint32_t SLOT_B = 16384;
constexpr int NT = 64;

#define P_NRF 11
#define P_NL2 21
#define P_REG_LO 120
#define P_REG_HI 192
#define P_SLEEP 200
#define P_LATE1 0
#define P_LATE2 0
#define P_NP0 9
#define P_NP1 0
#define P_NP3 9
#define P_PRE 2
#define P_START_NS 200
#define P_X 0
constexpr int NSB = 3;
constexpr int NB = 3 * NSB, NSLOT = 3 + NB;
constexpr int NRF = P_NRF;
constexpr int NL2 = P_NL2;
constexpr int NNR = NT - NB - NRF - NL2;
constexpr int TB = NT - NB;
constexpr int NZ = NRF + NL2;
static_assert(NNR >= P_X, "not enough filler");

constexpr int BAR_FULL = 0;
constexpr int BAR_RF = NSLOT, BAR_CAP = BAR_RF + 2 * NRF, BAR_FREE = BAR_CAP + 2 * NRF, BAR_DUMP = BAR_FREE + 2 * NRF;
constexpr int BAR_Q = BAR_DUMP + 2 * NRF, BAR_CTX = BAR_Q + 4, BAR_TAB = BAR_CTX + 4, BAR_W = BAR_TAB + 1, BAR_PRE = BAR_W + 2, NBAR = BAR_PRE + 4;

enum { F_NONE = 0, F_TILE = 1, F_KEEP = 2, F_FREE = 4, F_LATE = 8 };
constexpr uint32_t D_NOPROC = 1u << 12, D_FLUSH = 1u << 13, D_LAST = 1u << 20, D_END = 1u << 31;
constexpr uint32_t D_PRE = 1u << 21, D_RING = 1u << 22, D_CLAIM = 1u << 23, D_POOL = 1u << 24;
constexpr int NP0 = P_NP0, NP1 = P_NP1, NP3 = P_NP3;
struct Desc { uint32_t w0, w1; };
constexpr int LA = 68, LB = 42;
struct Tables {
    Desc a[3][LA];
    Desc b[3][LB];
    uint32_t inita[4];
    int capslot[2][NRF], dumpslot[2][NRF];
    bool ok;
};
enum { K_TILE = 0, K_CAP = 1, K_L2 = 2, K_DUMP = 4, K_RES = 5 };
struct Item { int kind, ctx, idx; };
constexpr uint32_t mk0(int bar, int par, int ctx, int slot) { return (uint32_t)(bar * 8) | ((uint32_t)par << 11) | ((uint32_t)ctx << 14) | ((uint32_t)slot << 16); }
constexpr uint32_t mkfill(const Item& x, int slot) {
    const int b = x.ctx & 1;
    if (x.kind == K_DUMP) return F_FREE | ((uint32_t)((BAR_FREE + b * NRF + x.idx - NNR) * 8) << 4);
    if (x.kind == K_RES) return F_NONE;
    const int bar = x.kind == K_CAP ? BAR_RF + b * NRF + x.idx - NNR : BAR_FULL + slot;
    return (x.kind == K_L2 ? F_KEEP : F_TILE) | ((uint32_t)(bar * 8) << 4) | ((uint32_t)(b * 8192 + 192 + x.idx) << 16);
}
constexpr Tables build_tables() {
    Tables T{};
    T.ok = true;
    Item A[256] = {};
    int n = 0;
    auto tiles = [&](int kind, int ctx, int lo, int hi) { for (int i = lo; i < hi; i++) A[n++] = Item{kind, ctx, i}; };
    tiles(K_TILE, 0, 0, NNR - NP0); tiles(K_CAP, 0, NNR, NNR + NRF); tiles(K_L2, 0, NNR + NRF, TB);
    tiles(K_TILE, 1, 0, NNR - NP1);
    tiles(K_TILE, 2, 0, P_X);
    tiles(K_CAP, 1, NNR, NNR + NRF); tiles(K_L2, 1, NNR + NRF, TB);
    tiles(K_TILE, 2, P_X, NNR);
    tiles(K_TILE, 3, 0, NNR - NP3);
    const int NA = n;
    for (int w = 0; w < 3; w++) {
        int m = 0, seen = 0, cur = -1;
        T.inita[w] = mkfill(A[w], w);
        for (int i = w; i < NA; i += 3) {
            const Item x = A[i];
            uint32_t fill = i + 3 < NA ? mkfill(A[i + 3], w) : (uint32_t)F_NONE;
            if ((x.ctx == 1 && x.idx < P_LATE1) || (x.ctx == 2 && x.idx >= P_X && x.idx < P_X + P_LATE2)) fill |= F_LATE;
            if (!((seen >> x.ctx) & 1)) { T.a[w][m++] = Desc{mk0(BAR_Q + x.ctx, 0, 0, w) | D_NOPROC, F_NONE}; seen |= 1 << x.ctx; }
            cur = x.ctx;
            int later = 0;
            for (int k = i + 3; k < NA; k += 3) if (A[k].ctx == cur) later = 1;
            uint32_t fl = (i + 3 >= NA || A[i + 3].ctx != cur) ? D_FLUSH : 0u;
            if (!later) fl |= D_LAST;
            int left = 0;
            for (int k = i + 3; k < NA; k += 3) if (A[k].ctx == cur) left++;
            const bool pooled = (cur == 0 && NP0) || (cur == 1 && NP1) || (cur == 3 && NP3);
            if (pooled && left == 0) { fl |= D_POOL; if (x.kind == K_CAP) T.ok = false; }
            if (pooled && left == 2) fl |= D_CLAIM;
            if (cur != 2 && w == 0 && left == (cur == 1 ? P_PRE : 0)) fl |= D_PRE;
            const int b = x.ctx & 1;
            if (x.kind == K_CAP) {
                T.capslot[b][x.idx - NNR] = w;
                T.a[w][m++] = Desc{mk0(BAR_RF + b * NRF + x.idx - NNR, 0, x.ctx, w) | fl, F_NONE};
                T.a[w][m++] = Desc{mk0(BAR_CAP + b * NRF + x.idx - NNR, 0, 0, w) | D_NOPROC, fill};
            } else {
                T.a[w][m++] = Desc{mk0(BAR_FULL + w, 0, x.ctx, w) | D_RING | fl, fill};
            }
        }
        if (seen != 15) T.ok = false;
        T.a[w][m++] = Desc{D_END, F_NONE};
        if (m > LA) T.ok = false;
        const int s0 = 3 + NSB * w;
        Item B[64] = {};
        int nb = 0;
        for (int h = 0; h < 2; h++) {
            for (int k = 0; k < NSB; k++) B[nb++] = Item{K_TILE, h, TB + s0 - 3 + k};
            for (int k = 0; k < NSB; k++) B[nb++] = Item{K_RES, 2 + h, 0};
            for (int z = 0; z < NZ; z++) if (z % 3 == w) B[nb++] = Item{z < NRF ? K_DUMP : K_TILE, 2 + h, NNR + z};
        }
        m = 0;
        int parb[NSB] = {};
        for (int k = 0; k < NSB; k++) T.b[w][m++] = Desc{mk0(BAR_FULL + (k ? s0 + k - 1 : w), 0, 0, s0 + k) | D_NOPROC, mkfill(B[k], s0 + k)};
        cur = -1;
        for (int i = 0; i < nb; i++) {
            const Item x = B[i];
            const int k = i % NSB, slot = s0 + k;
            const uint32_t fill = i + NSB < nb ? mkfill(B[i + NSB], slot) : (uint32_t)F_NONE;
            if (x.ctx != cur && x.kind != K_RES) T.b[w][m++] = Desc{mk0(BAR_Q + x.ctx, 0, 0, slot) | D_NOPROC, F_NONE};
            cur = x.ctx;
            const uint32_t fl = (i + 1 == nb || B[i + 1].ctx != cur) ? (D_FLUSH | D_LAST) : 0u;
            const int b = x.ctx & 1;
            if (x.kind == K_RES) T.b[w][m++] = Desc{mk0(BAR_Q + x.ctx, 0, x.ctx, slot) | fl, fill};
            else if (x.kind == K_DUMP) {
                T.dumpslot[b][x.idx - NNR] = slot;
                T.b[w][m++] = Desc{mk0(BAR_DUMP + b * NRF + x.idx - NNR, 0, x.ctx, slot) | fl, fill};
            } else { T.b[w][m++] = Desc{mk0(BAR_FULL + slot, parb[k], x.ctx, slot) | fl, fill}; parb[k] ^= 1; }
        }
        T.b[w][m++] = Desc{D_END, F_NONE};
        if (m > LB) T.ok = false;
    }
    return T;
}
constexpr Tables HT = build_tables();
static_assert(HT.ok, "schedule does not fit");
constexpr unsigned long long pack_slots(const int* v) { unsigned long long r = 0; for (int i = 0; i < NRF; i++) r |= (unsigned long long)v[i] << (4 * i); return r; }
constexpr unsigned long long CAP0 = pack_slots(HT.capslot[0]), CAP1 = pack_slots(HT.capslot[1]);
constexpr unsigned long long DUMP0 = pack_slots(HT.dumpslot[0]), DUMP1 = pack_slots(HT.dumpslot[1]);
constexpr uint32_t INITA0 = HT.inita[0], INITA1 = HT.inita[1], INITA2 = HT.inita[2];
static_assert(NRF <= 16, "slot packing");
__device__ const Tables g_tab = build_tables();
constexpr uint32_t TAB_BYTES = (3 * LA + 3 * LB) * 8;
static_assert(TAB_BYTES % 16 == 0, "bulk copy size");

constexpr uint32_t SM_W = NSLOT * SLOT_B;
constexpr uint32_t SM_Q = SM_W + 3 * 8192;
constexpr uint32_t SM_PART = SM_Q + 2048;
constexpr uint32_t XS = 1040;
constexpr uint32_t SM_XN = SM_PART + 6 * 528;
constexpr uint32_t SM_BIAS = SM_XN + 2 * XS;
constexpr uint32_t SM_V = SM_BIAS + 64;
constexpr uint32_t SM_TAB = SM_V + 160;
constexpr uint32_t SM_BAR = SM_TAB + TAB_BYTES;
constexpr uint32_t SM_TOTAL = SM_BAR + NBAR * 8;
static_assert(SM_TOTAL <= 232448 && NBAR * 8 < 2048, "shared memory budget");

#define P_R 8
constexpr int XR = P_R;
__device__ __align__(128) uint32_t g_opart[4][NCTA][160];
__device__ __align__(128) uint32_t g_qpart[4][NCTA][128];
__device__ __align__(128) uint32_t g_inbox[2][32][NCTA][16];
__device__ __align__(128) uint32_t g_xrow[2][8][1024];
__device__ unsigned g_epoch;
__device__ __align__(128) unsigned g_pool[2][32][4][8];
#define TS(i) do {} while (0)
#define TSYNC(k) do {} while (0)

struct Params {
    const __nv_bfloat16 *x, *k, *v, *b1, *b2;
    __nv_bfloat16* out;
    CUtensorMap mwq, mwo, mw1, mw2;
};

__device__ __forceinline__ void mbar_init(uint32_t bar, int cnt) { asm volatile("mbarrier.init.shared::cta.b64 [%0], %1;" ::"r"(bar), "r"(cnt)); }
__device__ __forceinline__ void mbar_expect_tx(uint32_t bar, uint32_t bytes) { asm volatile("mbarrier.arrive.expect_tx.shared::cta.b64 _, [%0], %1;" ::"r"(bar), "r"(bytes) : "memory"); }
__device__ __forceinline__ void mbar_arrive(uint32_t bar) { asm volatile("mbarrier.arrive.shared::cta.b64 _, [%0];" ::"r"(bar) : "memory"); }
__device__ __forceinline__ bool mbar_test(uint32_t bar, uint32_t parity) {
    uint32_t ok;
    asm volatile("{\n.reg .pred p;\nmbarrier.test_wait.parity.shared::cta.b64 p, [%1], %2;\nselp.u32 %0, 1, 0, p;\n}" : "=r"(ok) : "r"(bar), "r"(parity) : "memory");
    return ok;
}
__device__ __forceinline__ bool mbar_try(uint32_t bar, uint32_t parity) {
    uint32_t ok;
    asm volatile("{\n.reg .pred p;\nmbarrier.try_wait.parity.shared::cta.b64 p, [%1], %2;\nselp.u32 %0, 1, 0, p;\n}" : "=r"(ok) : "r"(bar), "r"(parity) : "memory");
    return ok;
}
__device__ __forceinline__ void mbar_wait(uint32_t bar, uint32_t parity) {
    uint32_t it = 0;
    while (!mbar_try(bar, parity)) { if (++it > (1u << 24)) __trap(); }
}
__device__ __forceinline__ void mbar_wait_long(uint32_t bar) {
    uint32_t it = 0, ok;
    do {
        asm volatile("{\n.reg .pred p;\nmbarrier.try_wait.parity.shared::cta.b64 p, [%1], 0, %2;\nselp.u32 %0, 1, 0, p;\n}" : "=r"(ok) : "r"(bar), "r"(2000u) : "memory");
        if (++it > (1u << 22)) __trap();
    } while (!ok);
}
__device__ __forceinline__ bool elect_one() {
    uint32_t r;
    asm volatile("{\n.reg .pred P;\nelect.sync _|P, 0xffffffff;\nselp.b32 %0, 1, 0, P;\n}" : "=r"(r));
    return r;
}
__device__ __forceinline__ bool mbar_test_warp(uint32_t bar, uint32_t parity) { return __all_sync(0xffffffffu, mbar_test(bar, parity)); }
__device__ __forceinline__ void bulk_g2s(uint32_t dst, const void* src, uint32_t bytes, uint32_t bar, uint64_t pol) {
    asm volatile("cp.async.bulk.shared::cluster.global.mbarrier::complete_tx::bytes.L2::cache_hint [%0], [%1], %2, [%3], %4;"
                 ::"r"(dst), "l"(src), "r"(bytes), "r"(bar), "l"(pol) : "memory");
}
__device__ __forceinline__ void bulk_prefetch(const void* src, uint32_t bytes) {
    asm volatile("cp.async.bulk.prefetch.L2.global [%0], %1;" ::"l"(src), "r"(bytes) : "memory");
}
__device__ __forceinline__ void ldsm4(uint32_t (&r)[4], uint32_t a) {
    asm volatile("ldmatrix.sync.aligned.m8n8.x4.shared.b16 {%0,%1,%2,%3}, [%4];" : "=r"(r[0]), "=r"(r[1]), "=r"(r[2]), "=r"(r[3]) : "r"(a));
}
__device__ __forceinline__ void ldsm4t(uint32_t (&r)[4], uint32_t a) {
    asm volatile("ldmatrix.sync.aligned.m8n8.x4.trans.shared.b16 {%0,%1,%2,%3}, [%4];" : "=r"(r[0]), "=r"(r[1]), "=r"(r[2]), "=r"(r[3]) : "r"(a));
}
__device__ __forceinline__ void mma16816(float (&c)[4], const uint32_t (&a)[4], uint32_t b0, uint32_t b1) {
    asm volatile("mma.sync.aligned.m16n8k16.row.col.f32.bf16.bf16.f32 {%0,%1,%2,%3}, {%4,%5,%6,%7}, {%8,%9}, {%0,%1,%2,%3};"
                 : "+f"(c[0]), "+f"(c[1]), "+f"(c[2]), "+f"(c[3]) : "r"(a[0]), "r"(a[1]), "r"(a[2]), "r"(a[3]), "r"(b0), "r"(b1));
}
__device__ __forceinline__ void lds128(uint32_t* r, uint32_t a) {
    asm volatile("ld.shared.v4.u32 {%0,%1,%2,%3}, [%4];" : "=r"(r[0]), "=r"(r[1]), "=r"(r[2]), "=r"(r[3]) : "r"(a) : "memory");
}
__device__ __forceinline__ void sts128(uint32_t a, const uint32_t* r) {
    asm volatile("st.shared.v4.u32 [%0], {%1,%2,%3,%4};" ::"r"(a), "r"(r[0]), "r"(r[1]), "r"(r[2]), "r"(r[3]) : "memory");
}
__device__ __forceinline__ uint32_t lds32(uint32_t a) { uint32_t r; asm volatile("ld.shared.u32 %0, [%1];" : "=r"(r) : "r"(a) : "memory"); return r; }
__device__ __forceinline__ uint32_t lds16(uint32_t a) { uint16_t r; asm volatile("ld.shared.u16 %0, [%1];" : "=h"(r) : "r"(a) : "memory"); return r; }
__device__ __forceinline__ float ldsf(uint32_t a) { float r; asm volatile("ld.shared.f32 %0, [%1];" : "=f"(r) : "r"(a) : "memory"); return r; }
__device__ __forceinline__ void sts32(uint32_t a, uint32_t v) { asm volatile("st.shared.u32 [%0], %1;" ::"r"(a), "r"(v) : "memory"); }
__device__ __forceinline__ void sts16(uint32_t a, uint32_t v) { asm volatile("st.shared.u16 [%0], %1;" ::"r"(a), "h"((uint16_t)v) : "memory"); }
__device__ __forceinline__ void stsf(uint32_t a, float v) { asm volatile("st.shared.f32 [%0], %1;" ::"r"(a), "f"(v) : "memory"); }
__device__ __forceinline__ void sts64(uint32_t a, uint32_t v0, uint32_t v1) { asm volatile("st.shared.v2.u32 [%0], {%1,%2};" ::"r"(a), "r"(v0), "r"(v1) : "memory"); }
__device__ __forceinline__ void cp16(uint32_t dst, const void* src) { asm volatile("cp.async.cg.shared.global [%0], [%1], 16;" ::"r"(dst), "l"(src) : "memory"); }
__device__ __forceinline__ float ex2(float x) { float r; asm("ex2.approx.ftz.f32 %0, %1;" : "=f"(r) : "f"(x)); return r; }
__device__ __forceinline__ uint32_t pack_bf16(float lo, float hi) { uint32_t r; asm("cvt.rn.bf16x2.f32 %0, %1, %2;" : "=r"(r) : "f"(hi), "f"(lo)); return r; }
__device__ __forceinline__ float bf_lo(uint32_t v) { return __uint_as_float(v << 16); }
__device__ __forceinline__ float bf_hi(uint32_t v) { return __uint_as_float(v & 0xffff0000u); }
__device__ __forceinline__ float bfr(float x) { return __bfloat162float(__float2bfloat16_rn(x)); }
__device__ __forceinline__ uint32_t ll_pack(float v, uint32_t tag) { return (__float_as_uint(v) & ~15u) | tag; }
__device__ __forceinline__ float ll_val(uint32_t w) { return __uint_as_float(w & ~15u); }
__device__ __forceinline__ void st_w(uint32_t* p, uint32_t w) { asm volatile("st.relaxed.gpu.global.u32 [%0], %1;" ::"l"(p), "r"(w) : "memory"); }
__device__ __forceinline__ void st_w4(uint32_t* p, uint32_t a, uint32_t b, uint32_t c, uint32_t d) {
    asm volatile("st.relaxed.gpu.global.v4.u32 [%0], {%1,%2,%3,%4};" ::"l"(p), "r"(a), "r"(b), "r"(c), "r"(d) : "memory");
}
__device__ __forceinline__ void ll_store(uint32_t* p, float v, uint32_t tag) { st_w(p, ll_pack(v, tag)); }
__device__ __forceinline__ void ld_w4(const uint32_t* p, bool pred, uint32_t (&w)[4]) {
    asm volatile("{\n.reg .pred q;\nsetp.ne.u32 q, %5, 0;\n@q ld.relaxed.gpu.global.v4.u32 {%0,%1,%2,%3}, [%4];\n}"
                 : "+r"(w[0]), "+r"(w[1]), "+r"(w[2]), "+r"(w[3]) : "l"(p), "r"((uint32_t)pred) : "memory");
}
__device__ __forceinline__ void ld_w2(const uint32_t* p, bool pred, uint32_t& a, uint32_t& b) {
    asm volatile("{\n.reg .pred q;\nsetp.ne.u32 q, %3, 0;\n@q ld.relaxed.gpu.global.v2.u32 {%0,%1}, [%2];\n}" : "+r"(a), "+r"(b) : "l"(p), "r"((uint32_t)pred) : "memory");
}
__device__ __forceinline__ void ld_w1(const uint32_t* p, bool pred, uint32_t& a) {
    asm volatile("{\n.reg .pred q;\nsetp.ne.u32 q, %2, 0;\n@q ld.relaxed.gpu.global.u32 %0, [%1];\n}" : "+r"(a) : "l"(p), "r"((uint32_t)pred) : "memory");
}
__device__ __forceinline__ bool miss4(const uint32_t (&w)[4], uint32_t tag) { return (((w[0] ^ tag) | (w[1] ^ tag) | (w[2] ^ tag) | (w[3] ^ tag)) & 15u) != 0; }
#define SPIN_GUARD(it) do { if (++(it) > (1u << 22)) __trap(); } while (0)

struct PVB { uint32_t x0, x1, y0, y1; };
struct LaneC {
    int g, t, v;
    int src0, src1;
    uint32_t sx0, sy0;
    uint32_t voff;
    int vrow;
};
__device__ __forceinline__ PVB spread(uint32_t pk, const LaneC& L) {
    uint32_t v0 = __shfl_sync(0xffffffffu, pk, L.src0), v1 = __shfl_sync(0xffffffffu, pk, L.src1);
    PVB b;
    b.x0 = __byte_perm(v0, 0, L.sx0); b.y0 = __byte_perm(v0, 0, L.sy0);
    b.x1 = __byte_perm(v1, 0, L.sx0 ^ 0x5454u); b.y1 = __byte_perm(v1, 0, L.sy0 ^ 0x7676u);
    return b;
}
__device__ __forceinline__ void pv_load(uint32_t (&a)[8][4], uint32_t base) {
#pragma unroll
    for (int c = 0; c < 8; c++) ldsm4t(a[c], base ^ (c << 4));
}
template <int U> __device__ __forceinline__ void unit_load(uint32_t (&r)[16], uint32_t a) {
    asm volatile("ld.shared.v4.u32 {%0,%1,%2,%3}, [%16];\nld.shared.v4.u32 {%4,%5,%6,%7}, [%16+512];\n"
                 "ld.shared.v4.u32 {%8,%9,%10,%11}, [%16+1024];\nld.shared.v4.u32 {%12,%13,%14,%15}, [%16+1536];\nmembar.cta; // %17"
                 : "=r"(r[0]), "=r"(r[1]), "=r"(r[2]), "=r"(r[3]), "=r"(r[4]), "=r"(r[5]), "=r"(r[6]), "=r"(r[7]), "=r"(r[8]), "=r"(r[9]),
                   "=r"(r[10]), "=r"(r[11]), "=r"(r[12]), "=r"(r[13]), "=r"(r[14]), "=r"(r[15]) : "r"(a), "n"(U) : "memory");
}
template <int U> __device__ __forceinline__ void unit_store(const uint32_t (&r)[16], uint32_t a) {
    asm volatile("st.shared.v4.u32 [%16], {%0,%1,%2,%3};\nst.shared.v4.u32 [%16+512], {%4,%5,%6,%7};\n"
                 "st.shared.v4.u32 [%16+1024], {%8,%9,%10,%11};\nst.shared.v4.u32 [%16+1536], {%12,%13,%14,%15};\nfence.proxy.async.shared::cta; // %17"
                 :: "r"(r[0]), "r"(r[1]), "r"(r[2]), "r"(r[3]), "r"(r[4]), "r"(r[5]), "r"(r[6]), "r"(r[7]), "r"(r[8]), "r"(r[9]),
                    "r"(r[10]), "r"(r[11]), "r"(r[12]), "r"(r[13]), "r"(r[14]), "r"(r[15]), "r"(a), "n"(U) : "memory");
}
template <int LO, int HI, bool LOAD> __device__ __forceinline__ void unit_dispatch(uint32_t (&r)[NRF][16], int u, uint32_t a) {
    if constexpr (HI - LO == 1) {
        if constexpr (LOAD) unit_load<LO>(r[LO], a); else unit_store<LO>(r[LO], a);
    } else {
        constexpr int MID = (LO + HI) / 2;
        if (u < MID) unit_dispatch<LO, MID, LOAD>(r, u, a); else unit_dispatch<MID, HI, LOAD>(r, u, a);
    }
}

struct Ctx { float o[4]; float m, l; };
constexpr float SCL = 0.08838834764831845f * 1.4426950408889634f;

__device__ __forceinline__ void process_tile(Ctx& S, uint32_t tile, uint32_t qaddr, uint32_t koff, uint32_t voff, const LaneC& L,
                                             uint32_t fill, uint32_t bars, const char* kbase, const char* vbase, uint64_t pol) {
    float sa0[4] = {0.f, 0.f, 0.f, 0.f}, sa1[4] = {0.f, 0.f, 0.f, 0.f}, sb0[4] = {0.f, 0.f, 0.f, 0.f}, sb1[4] = {0.f, 0.f, 0.f, 0.f};
    const uint32_t kb = tile + koff;
    {
        uint32_t q[4][4], a[4][4][4];
#pragma unroll
        for (int i = 0; i < 4; i++) {
            lds128(q[i], qaddr ^ (i << 4));
            const uint32_t k0 = kb ^ ((2 * i) << 5), k1 = kb ^ ((2 * i + 1) << 5);
            ldsm4(a[i][0], k0); ldsm4(a[i][1], k1); ldsm4(a[i][2], k0 + 4096); ldsm4(a[i][3], k1 + 4096);
            if (i > 0) {
                mma16816(sa0, a[i - 1][0], q[i - 1][0], q[i - 1][1]); mma16816(sa1, a[i - 1][1], q[i - 1][2], q[i - 1][3]);
                mma16816(sb0, a[i - 1][2], q[i - 1][0], q[i - 1][1]); mma16816(sb1, a[i - 1][3], q[i - 1][2], q[i - 1][3]);
            }
        }
        mma16816(sa0, a[3][0], q[3][0], q[3][1]); mma16816(sa1, a[3][1], q[3][2], q[3][3]);
        mma16816(sb0, a[3][2], q[3][0], q[3][1]); mma16816(sb1, a[3][3], q[3][2], q[3][3]);
    }
    const uint32_t vb = tile + voff;
    uint32_t av[8][4];
    pv_load(av, vb);
    const bool refill = ((fill & 7) - 1u) < 2u;
    const uint32_t fbar = bars + ((fill >> 4) & 0x7ff);
    const uint32_t foff = (fill >> 16) << 13;
    if (refill && !(fill & F_LATE) && elect_one()) {
        mbar_expect_tx(fbar, SLOT_B);
        bulk_g2s(tile, kbase + foff, HALF_B, fbar, pol);
        if (fill & 2) bulk_prefetch(kbase + foff, HALF_B);
    }
    __syncwarp();
    const bool odd = L.g & 1;
    const bool valid = (L.v == 0);
    const float s0 = (odd ? sa0[1] + sa1[1] : sa0[0] + sa1[0]) * SCL, s1 = (odd ? sa0[3] + sa1[3] : sa0[2] + sa1[2]) * SCL;
    const float s2 = (odd ? sb0[1] + sb1[1] : sb0[0] + sb1[0]) * SCL, s3 = (odd ? sb0[3] + sb1[3] : sb0[2] + sb1[2]) * SCL;
    float mx = valid ? fmaxf(fmaxf(s0, s1), fmaxf(s2, s3)) : -INFINITY;
    if (__any_sync(0xffffffffu, mx > S.m)) {
#pragma unroll
        for (int o = 16; o > 0; o >>= 1) mx = fmaxf(mx, __shfl_xor_sync(0xffffffffu, mx, o));
        const float f = ex2(S.m - mx);
        S.o[0] *= f; S.o[1] *= f; S.o[2] *= f; S.o[3] *= f; S.l *= f;
        S.m = mx;
    }
    const float p0 = ex2(s0 - S.m), p1 = ex2(s1 - S.m), p2 = ex2(s2 - S.m), p3 = ex2(s3 - S.m);
    if (valid) S.l += (p0 + p1) + (p2 + p3);
    const PVB ba = spread(pack_bf16(p0, p1), L), bb = spread(pack_bf16(p2, p3), L);
    float o1[4] = {0.f, 0.f, 0.f, 0.f}, o2[4] = {0.f, 0.f, 0.f, 0.f}, o3[4] = {0.f, 0.f, 0.f, 0.f};
#pragma unroll
    for (int c = 0; c < 8; c += 2) {
        const bool on = (L.v == (c >> 1));
        uint32_t w0[4], w1[4];
        ldsm4t(w0, (vb ^ (c << 4)) + 4096); ldsm4t(w1, (vb ^ ((c + 1) << 4)) + 4096);
        mma16816(S.o, av[c], on ? ba.x0 : 0u, on ? ba.y0 : 0u);
        mma16816(o1, av[c + 1], on ? ba.x1 : 0u, on ? ba.y1 : 0u);
        mma16816(o2, w0, on ? bb.x0 : 0u, on ? bb.y0 : 0u);
        mma16816(o3, w1, on ? bb.x1 : 0u, on ? bb.y1 : 0u);
    }
    if (refill && elect_one()) {
        if (fill & F_LATE) {
            mbar_expect_tx(fbar, SLOT_B);
            bulk_g2s(tile, kbase + foff, HALF_B, fbar, pol);
            if (fill & 2) bulk_prefetch(kbase + foff, HALF_B);
        }
        bulk_g2s(tile + HALF_B, vbase + foff, HALF_B, fbar, pol);
        if (fill & 2) bulk_prefetch(vbase + foff, HALF_B);
    }
    __syncwarp();
    S.o[0] += o1[0] + (o2[0] + o3[0]); S.o[1] += o1[1] + (o2[1] + o3[1]);
    S.o[2] += o1[2] + (o2[2] + o3[2]); S.o[3] += o1[3] + (o2[3] + o3[3]);
}

__device__ __forceinline__ void flush_ctx(Ctx& S, uint32_t part, bool first, int lane, const LaneC& L) {
    float l = S.l;
#pragma unroll
    for (int o = 16; o > 0; o >>= 1) l += __shfl_xor_sync(0xffffffffu, l, o);
    const uint32_t a = part + (16 * L.t + L.g) * 4;
    float m = S.m;
    if (!first) {
        const float mo = ldsf(part + 512), lo = ldsf(part + 516);
        m = fmaxf(mo, S.m);
        const float fo = ex2(mo - m), fn = ex2(S.m - m);
        S.o[0] = S.o[0] * fn + ldsf(a) * fo; S.o[1] = S.o[1] * fn + ldsf(a + 32) * fo;
        S.o[2] = S.o[2] * fn + ldsf(a + 256) * fo; S.o[3] = S.o[3] * fn + ldsf(a + 288) * fo;
        l = l * fn + lo * fo;
        __syncwarp();
    }
    stsf(a, S.o[0]); stsf(a + 32, S.o[1]); stsf(a + 256, S.o[2]); stsf(a + 288, S.o[3]);
    if (lane == 0) { stsf(part + 512, m); stsf(part + 516, l); }
    S.o[0] = S.o[1] = S.o[2] = S.o[3] = 0.f; S.l = 0.f; S.m = -INFINITY;
    __syncwarp();
}

template <bool PF> __device__ __forceinline__ void tma2d(uint32_t dst, const CUtensorMap* map, int c0, int c1, uint32_t bar, uint64_t pol) {
    if (PF) asm volatile("cp.async.bulk.prefetch.tensor.2d.L2.global.tile [%0, {%1, %2}];" ::"l"(map), "r"(c0), "r"(c1) : "memory");
    else asm volatile("cp.async.bulk.tensor.2d.shared::cluster.global.tile.mbarrier::complete_tx::bytes.L2::cache_hint [%0], [%1, {%2, %3}], [%4], %5;"
                      ::"r"(dst), "l"(map), "r"(c0), "r"(c1), "r"(bar), "l"(pol) : "memory");
}
template <int ST, int I, bool PF> __device__ __forceinline__ void load_chunk(const Params& p, uint32_t dst, uint32_t bar, uint64_t pol) {
    const int cta = blockIdx.x;
    if (ST == 0) {
        tma2d<PF>(dst, &p.mwo, 128 * I, 32 * cta, bar, pol); tma2d<PF>(dst + 4096, &p.mwo, 128 * I + 64, 32 * cta, bar, pol);
    } else if (ST == 1 && I < 2) {
        tma2d<PF>(dst, &p.mw1, 16 * cta, 256 * I, bar, pol);
    } else if (ST == 1) {
#pragma unroll
        for (int i = 0; i < 4; i++) tma2d<PF>(dst + i * 2048, &p.mw2, 256 * (I - 2) + 64 * i, 16 * cta, bar, pol);
    } else {
        const int r = 128 * (cta & 3) + 32 * I, cc = 128 * (cta >> 2);
        tma2d<PF>(dst, &p.mwq, cc, r, bar, pol); tma2d<PF>(dst + 4096, &p.mwq, cc + 64, r, bar, pol);
    }
}
struct WBuf {
    uint32_t a[3], bar, par;
    __device__ __forceinline__ void wait3() { mbar_wait(bar, par); }
    __device__ __forceinline__ void wait4() { mbar_wait(bar + 8, par); }
    __device__ __forceinline__ void rotate() { const uint32_t x = a[0]; a[0] = a[1]; a[1] = a[2]; a[2] = x; par ^= 1; }
};
template <int ST, bool PF4> __device__ __forceinline__ void load_stage1(const Params& p, const WBuf& W, uint64_t pol) {
    if (ST == 1 && blockIdx.x >= NMLP) { mbar_arrive(W.bar); mbar_arrive(W.bar + 8); return; }
    mbar_expect_tx(W.bar, 3 * 8192);
    load_chunk<ST, 0, false>(p, W.a[0], W.bar, pol);
    load_chunk<ST, 1, false>(p, W.a[1], W.bar, pol);
    load_chunk<ST, 2, false>(p, W.a[2], W.bar, pol);
    if (PF4) load_chunk<ST, 3, true>(p, 0, 0, pol);
}
template <int ST, bool PF4> __device__ __forceinline__ void load_stage(const Params& p, const WBuf& W, uint64_t pol) {
    __syncwarp();
    if (elect_one()) load_stage1<ST, PF4>(p, W, pol);
    __syncwarp();
}
template <int ST> __device__ __forceinline__ void load_fourth(const Params& p, const WBuf& W, uint64_t pol) {
    __syncwarp();
    if (elect_one()) { mbar_expect_tx(W.bar + 8, 8192); load_chunk<ST, 3, false>(p, W.a[0], W.bar + 8, pol); }
    __syncwarp();
}
__device__ __forceinline__ void frag8(uint32_t (&f)[8][4], uint32_t a) {
#pragma unroll
    for (int u = 0; u < 4; u++) { ldsm4t(f[u], a ^ (u << 5)); ldsm4t(f[4 + u], (a ^ (u << 5)) + 2048); }
}
template <int N, int STRIDE, int HALF> __device__ __forceinline__ void ll_gather(const uint32_t* src, int n, uint32_t tag, uint32_t (&w)[N][4]) {
#pragma unroll
    for (int i = 0; i < N; i++) w[i][0] = w[i][1] = w[i][2] = w[i][3] = i < n ? 0u : tag;
    uint32_t it = 0;
    while (true) {
#pragma unroll
        for (int i = 0; i < N; i++) ld_w4(src + (HALF ? (i & 3) * STRIDE + (i >> 2) * HALF : i * STRIDE), miss4(w[i], tag), w[i]);
        bool miss = false;
#pragma unroll
        for (int i = 0; i < N; i++) miss |= miss4(w[i], tag);
        if (!__any_sync(0xffffffffu, miss)) break;
        SPIN_GUARD(it);
    }
}
__device__ __forceinline__ void pick4(float (&o)[4], const float (&a0)[4], const float (&a1)[4], const float (&a2)[4], const float (&a3)[4], int t) {
#pragma unroll
    for (int i = 0; i < 4; i++) o[i] = (t & 2) ? ((t & 1) ? a3[i] : a2[i]) : ((t & 1) ? a1[i] : a0[i]);
}
__device__ __forceinline__ void issue_fill(uint32_t fill, uint32_t dst, uint32_t bars, const char* kbase, const char* vbase, uint64_t pol) {
    const uint32_t fbar = bars + ((fill >> 4) & 0x7ff);
    const uint32_t foff = (fill >> 16) << 13;
    mbar_expect_tx(fbar, SLOT_B);
    bulk_g2s(dst, kbase + foff, HALF_B, fbar, pol);
    bulk_g2s(dst + HALF_B, vbase + foff, HALF_B, fbar, pol);
    if (fill & 2) { bulk_prefetch(kbase + foff, HALF_B); bulk_prefetch(vbase + foff, HALF_B); }
}
__device__ __forceinline__ uint2 lds64u(uint32_t a) {
    uint2 r;
    asm volatile("ld.shared.v2.u32 {%0,%1}, [%2];" : "=r"(r.x), "=r"(r.y) : "r"(a) : "memory");
    r.x = __shfl_sync(0xffffffffu, r.x, 0); r.y = __shfl_sync(0xffffffffu, r.y, 0);
    return r;
}

__device__ __forceinline__ float gelu_tanh(float x) {
    const float u = 0.7978845608028654f * (x + 0.044715f * x * x * x);
    const float th = 1.f - 2.f / (__expf(2.f * u) + 1.f);
    return 0.5f * x * (1.f + th);
}

__device__ __forceinline__ void fill_ones(uint32_t a, int lane) {
    const uint32_t o[4] = {0x3f803f80u, 0x3f803f80u, 0x3f803f80u, 0x3f803f80u};
    sts128(a + lane * 16, o); sts128(a + 512 + lane * 16, o);
}
__device__ __forceinline__ void ln_store2(const float (&x)[2][16], uint32_t xn, int lane) {
    float s[2] = {0.f, 0.f}, q[2] = {0.f, 0.f};
#pragma unroll
    for (int i = 0; i < 32; i++) s[i >> 4] += x[i >> 4][i & 15];
#pragma unroll
    for (int o = 16; o > 0; o >>= 1) { s[0] += __shfl_xor_sync(0xffffffffu, s[0], o); s[1] += __shfl_xor_sync(0xffffffffu, s[1], o); }
    s[0] *= (1.f / DM); s[1] *= (1.f / DM);
#pragma unroll
    for (int i = 0; i < 32; i++) { const float d = x[i >> 4][i & 15] - s[i >> 4]; q[i >> 4] += d * d; }
#pragma unroll
    for (int o = 16; o > 0; o >>= 1) { q[0] += __shfl_xor_sync(0xffffffffu, q[0], o); q[1] += __shfl_xor_sync(0xffffffffu, q[1], o); }
#pragma unroll
    for (int b = 0; b < 2; b++) {
        const float r = rsqrtf(q[b] * (1.f / DM) + 1e-5f), mean = s[b];
#pragma unroll
        for (int i = 0; i < 4; i++)
            sts64(xn + b * XS + (128 * i + 4 * lane) * 2, pack_bf16((x[b][4 * i] - mean) * r, (x[b][4 * i + 1] - mean) * r),
                  pack_bf16((x[b][4 * i + 2] - mean) * r, (x[b][4 * i + 3] - mean) * r));
    }
}

__global__ void __launch_bounds__(384, 1) fused_kernel(const __grid_constant__ Params p) {
    extern __shared__ __align__(1024) unsigned char smem_raw[];
    const uint32_t sb = (uint32_t)__cvta_generic_to_shared(smem_raw);
    const int tid = threadIdx.x, lane = tid & 31;
    const int warp = __shfl_sync(0xffffffffu, tid >> 5, 0);
    const int cta = blockIdx.x;

    const uint32_t bars = sb + SM_BAR;
    if (tid == 0) TSYNC(0);
    uint64_t pol;
    asm volatile("createpolicy.fractional.L2::evict_first.b64 %0, 1.0;" : "=l"(pol));
    const char* kbase = reinterpret_cast<const char*>(p.k) + ((ptrdiff_t)(cta - 3) << 19);
    const char* vbase = reinterpret_cast<const char*>(p.v) + ((ptrdiff_t)(cta - 3) << 19);
    WBuf W;
    W.a[0] = sb + SM_W; W.a[1] = sb + SM_W + 8192; W.a[2] = sb + SM_W + 16384; W.bar = bars + BAR_W * 8; W.par = 0;
    uint32_t epoch = 0;
    if (warp < 4) asm volatile("ld.relaxed.gpu.global.u32 %0, [%1];" : "=r"(epoch) : "l"(&g_epoch) : "memory");
    if (warp == 3) {
#pragma unroll
        for (int i = 0; i < 4; i++) cp16(sb + SM_XN + (i >> 1) * XS + (i & 1) * 512 + lane * 16, p.x + 256 * i + 8 * lane);
        if (lane < 2) cp16(sb + SM_BIAS + lane * 16, p.b2 + 16 * (cta & 31) + 8 * lane);
        else if (lane < 4 && cta < NMLP) cp16(sb + SM_BIAS + lane * 16, p.b1 + 16 * cta + 8 * (lane - 2));
        if (elect_one()) {
            asm volatile("prefetch.tensormap [%0];" ::"l"(&p.mwq) : "memory");
            mbar_init(W.bar, 1); mbar_init(W.bar + 8, 1);
            asm volatile("fence.mbarrier_init.release.cluster;" ::: "memory");
            load_stage1<2, true>(p, W, pol);
        }
    } else if (warp == 0) {
        if (elect_one()) {
#pragma unroll
            for (int k = 0; k < 3; k++) mbar_init(bars + (BAR_FULL + k) * 8, 1);
            mbar_init(bars + BAR_TAB * 8, 1);
            asm volatile("fence.mbarrier_init.release.cluster;" ::: "memory");
            __nanosleep(P_START_NS);
            issue_fill(INITA0, sb, bars, kbase, vbase, pol);
            issue_fill(INITA1, sb + SLOT_B, bars, kbase, vbase, pol);
            issue_fill(INITA2, sb + 2 * SLOT_B, bars, kbase, vbase, pol);
            mbar_expect_tx(bars + BAR_TAB * 8, TAB_BYTES);
            asm volatile("cp.async.bulk.shared::cluster.global.mbarrier::complete_tx::bytes [%0], [%1], %2, [%3];"
                         ::"r"(sb + SM_TAB), "l"(&g_tab), "r"(TAB_BYTES), "r"(bars + BAR_TAB * 8) : "memory");
        }
    } else if (warp >= 4) {
        const int i = tid - 128 + 3;
        if (i < NBAR && i != BAR_TAB && (i < BAR_W || i >= BAR_W + 2)) {
            int cnt = 1;
            if ((i >= BAR_CAP && i < BAR_FREE) || (i >= BAR_DUMP && i < BAR_Q)) cnt = 8;
            if (i >= BAR_CTX && i < BAR_TAB) cnt = 6;
            mbar_init(bars + i * 8, cnt);
            asm volatile("fence.mbarrier_init.release.cluster;" ::: "memory");
        }
    }
    static_assert(NBAR <= 256, "set-up mapping");
    __syncthreads();

    if (warp >= 4) {
        asm volatile("setmaxnreg.inc.sync.aligned.u32 %0;" ::"n"(P_REG_HI));
        const uint32_t mine = sb + (warp - 4) * 2048 + lane * 16;
        uint32_t r[NRF][16];
#pragma unroll
        for (int u = 0; u < NRF; u++)
#pragma unroll
            for (int c = 0; c < 16; c++) r[u][c] = 0;
        int nc = 0, nd = 0, uc = 0, ud = 0;
        unsigned long long cs = CAP0, ds = DUMP0;
        uint32_t it = 0;
        while (nd < 2 * NRF) {
            const bool canD = nd < nc, canC = nc < 2 * NRF && nc < nd + NRF;
            const uint32_t bd = bars + (BAR_FREE + nd) * 8, bc = bars + (BAR_RF + nc) * 8;
            if (!canC) mbar_wait_long(bd);
            if (!canD) mbar_wait_long(bc);
            if (canC && mbar_test_warp(bc, 0)) {
                unit_dispatch<0, NRF, true>(r, uc, mine + (uint32_t)(cs & 15) * SLOT_B);
                __syncwarp();
                if (lane == 0) mbar_arrive(bc + (BAR_CAP - BAR_RF) * 8);
                nc++; cs >>= 4;
                if (++uc == NRF) { uc = 0; cs = CAP1; }
                it = 0;
            } else if (canD && mbar_test_warp(bd, 0)) {
                unit_dispatch<0, NRF, false>(r, ud, mine + (uint32_t)(ds & 15) * SLOT_B);
                __syncwarp();
                if (lane == 0) mbar_arrive(bd + (BAR_DUMP - BAR_FREE) * 8);
                nd++; ds >>= 4;
                if (++ud == NRF) { ud = 0; ds = DUMP1; }
                it = 0;
            } else {
                __nanosleep(P_SLEEP);
                if (++it > (1u << 24)) __trap();
            }
        }
    } else {
        asm volatile("setmaxnreg.dec.sync.aligned.u32 %0;" ::"n"(P_REG_LO));
        LaneC L;
        L.g = lane >> 2; L.t = lane & 3; L.v = (L.g >> 1) ^ L.t;
        L.src0 = 9 * L.t + 4 * (L.g & 1); L.src1 = 9 * L.t + 4 * ((L.g & 1) ^ 1);
        L.sx0 = (L.g & 1) ? 0x1044u : 0x4410u; L.sy0 = (L.g & 1) ? 0x3244u : 0x4432u;
        L.vrow = (lane & 7) + 8 * (lane >> 4);
        L.voff = ((lane >> 3) & 1) * 128 + ((lane & 7) << 4);

        if (warp < 3) {
            const int w = warp;
            const uint32_t koff = ((lane & 7) + 8 * ((lane >> 3) & 1)) * 256 + (((lane >> 4) ^ (lane & 7)) << 4);
            const uint32_t voff = HALF_B + L.vrow * 256 + L.voff;
            const int qrow = 4 * (L.g & 3) + L.t;
            const uint32_t qoff = sb + SM_Q + qrow * 64 + (((L.g >> 2) ^ ((qrow >> 1) & 3)) << 4);
            Ctx SA, SB;
            SA.o[0] = SA.o[1] = SA.o[2] = SA.o[3] = 0.f; SA.l = 0.f; SA.m = -INFINITY;
            SB = SA;
            uint32_t pa = sb + SM_TAB + w * LA * 8, pb = sb + SM_TAB + (3 * LA + w * LB) * 8;
            mbar_wait(bars + BAR_TAB * 8, 0);
            uint2 dA = lds64u(pa), dB = lds64u(pb);
            uint32_t flushed = 0, idle = 0, parA = 0, claim = 0;
            auto run = [&](const uint2 d, Ctx& S, int ring) {
                const uint32_t tile = sb + ((d.x >> 16) & 15) * SLOT_B;
                const int ctx = (d.x >> 14) & 3;
                if (!(d.x & D_NOPROC)) process_tile(S, tile, qoff + (ctx & 1) * 1024, koff, voff, L, d.y, bars, kbase, vbase, pol);
                else if (((d.y & 7) - 1u) < 2u) {
                    if (elect_one()) issue_fill(d.y, tile, bars, kbase, vbase, pol);
                    __syncwarp();
                }
                if ((d.y & 7) == F_FREE) { if (lane == 0) mbar_arrive(bars + ((d.y >> 4) & 0x7ff)); }
                if (d.x & D_FLUSH) {
                    flush_ctx(S, sb + SM_PART + ((ctx & 1) * 3 + w) * 528, !((flushed >> ctx) & 1), lane, L);
                    flushed |= 1u << ctx;
                    if ((d.x & D_LAST) && lane == 0) mbar_arrive(bars + (BAR_CTX + ctx) * 8);
                    TS(ring * 12 + ctx * 3 + w);
                }
            };
            while (true) {
                uint2 d;
                if (!(dA.x & D_END) && mbar_test_warp(bars + (dA.x & 0x7ff), (dA.x >> 22) & parA)) {
                    d = dA;
                    parA ^= (d.x >> 22) & 1;
                    bool again = false;
                    if (d.x & (D_POOL | D_CLAIM | D_PRE)) {
                        const int ctx = (d.x >> 14) & 3;
                        if (d.x & D_PRE) { if (lane == 0) mbar_arrive(bars + (BAR_PRE + ctx) * 8); dA.x &= ~D_PRE; }
                        if (d.x & D_POOL) {
                            const uint32_t c = __shfl_sync(0xffffffffu, claim, 0);
                            const uint32_t np = ctx == 0 ? NP0 : (ctx == 1 ? NP1 : NP3);
                            if (c < 4 * np) {
                                again = true;
                                d.x &= ~D_FLUSH;
                                d.y = F_TILE | ((BAR_FULL + w) * 8 << 4) | (((ctx & 1) * 8192 + ((c & 3) - (cta & 3) + 3) * 64 + NNR - np + (c >> 2)) << 16);
                            }
                        }
                        if ((again || (d.x & D_CLAIM)) && lane == 0)
                            asm volatile("atom.relaxed.gpu.global.add.u32 %0, [%1], 1;" : "=r"(claim) : "l"(&g_pool[epoch & 1][cta >> 2][ctx][0]) : "memory");
                    }
                    if (!again) { pa += 8; dA = lds64u(pa); }
                    run(d, SA, 0);
                    if (!again) TS(128 + w * (LA + LB - 2 * LA) + ((pa - 8 - sb - SM_TAB) >> 3) + w * LA);
                } else if (!(dB.x & D_END) && mbar_test_warp(bars + (dB.x & 0x7ff), (dB.x >> 11) & 1)) {
                    d = dB; pb += 8; dB = lds64u(pb);
                    run(d, SB, 1);
                    TS(128 + w * (LA + LB) + LA + ((pb - 8 - sb - SM_TAB - (3 * LA + w * LB) * 8) >> 3));
                } else {
                    if (dA.x & dB.x & D_END) break;
                    if (++idle > (1u << 25)) __trap();
                    continue;
                }
                idle = 0;
            }
        } else {
            TS(24);
            if ((cta & 3) == 0) (&g_pool[(epoch & 1) ^ 1][cta >> 2][0][0])[lane] = 0;
            const int ob = cta >= 96 ? 0 : 1, oo = cta & 31;
            float xown[4], b2own[4];
            asm volatile("cp.async.wait_all;" ::: "memory");
            __syncwarp();
            {
                uint2 xv, bv;
                xv.x = lds32(sb + SM_XN + ob * XS + (16 * oo + 4 * (lane & 3)) * 2); xv.y = lds32(sb + SM_XN + ob * XS + (16 * oo + 4 * (lane & 3)) * 2 + 4);
                bv.x = lds32(sb + SM_BIAS + (lane & 3) * 8); bv.y = lds32(sb + SM_BIAS + (lane & 3) * 8 + 4);
                xown[0] = bf_lo(xv.x); xown[1] = bf_hi(xv.x); xown[2] = bf_lo(xv.y); xown[3] = bf_hi(xv.y);
                b2own[0] = bf_lo(bv.x); b2own[1] = bf_hi(bv.x); b2own[2] = bf_lo(bv.y); b2own[3] = bf_hi(bv.y);
            }
            const float bias = cta < NMLP ? bf_lo(lds16(sb + SM_BIAS + 32 + (L.g + 4 * (L.t & 2)) * 2)) : 0.f;
            const uint32_t tag0 = epoch % 15u + 1u, ubase = (epoch % 15u) * 6u;
            const uint32_t xnb = sb + SM_XN;
            const uint32_t aoff = L.vrow * 128 + ((((lane >> 3) & 1) ^ (lane & 7)) << 4);
            constexpr int OB = 32 * NCTA * 16;
#pragma unroll 1
            for (int gi = 0; gi < 4; gi++) {
                const int h = cta >> 2, j = cta & 3;
                const int bb0 = (gi == 2) ? 1 : 0, nb = (gi == 0 || gi == 3) ? 2 : 1;
                const bool owner = cta >= 64 && ob >= bb0 && ob < bb0 + nb;
                const uint32_t vb = sb + SM_V + (nb == 2 ? (lane & 1) * 80 : 0) + (lane >> 3) * 16;
                const uint32_t xb = (gi == 3 && (lane & 2) ? sb : xnb + (lane & 1) * XS) + (lane >> 3) * 16;
                uint32_t* const outbox = &g_inbox[bb0][L.t][cta][L.g];
                uint32_t* const qout = g_qpart[(gi ? 2 : 0) + bb0][cta] + 16 * L.t + L.g;
                uint32_t* const xout = &g_xrow[ob][(lane >> 2) % XR][16 * oo + 4 * (lane & 3)];
                auto reset_words = [&]() {
                    for (int bi = 0; bi < nb; bi++) {
                        if (gi) {
#pragma unroll
                            for (int i = 0; i < 8; i++) { st_w(outbox + bi * OB + i * 4 * NCTA * 16, 0); st_w(outbox + bi * OB + i * 4 * NCTA * 16 + 8, 0); }
                        }
                        if (gi < 3) { st_w(qout + bi * NCTA * 128, 0); st_w(qout + bi * NCTA * 128 + 8, 0); st_w(qout + bi * NCTA * 128 + 64, 0); st_w(qout + bi * NCTA * 128 + 72, 0); }
                    }
                    if (gi) {
                        uint32_t* dst = g_opart[gi == 3 ? 3 : bb0][cta];
#pragma unroll
                        for (int i = 0; i < 4; i++) st_w(dst + lane + 32 * i, 0);
                        if (lane < 8) st_w(dst + 128 + lane, 0);
                        if (owner && lane < 4 * XR) st_w4(xout, 0, 0, 0, 0);
                        if (elect_one()) load_chunk<0, 3, true>(p, 0, 0, pol);
                        __syncwarp();
                    }
                };
                if (gi == 1 || gi == 2) mbar_wait_long(bars + (BAR_PRE + gi - 1) * 8);
                if (gi < 3) reset_words();
#pragma unroll 1
                for (int st = (gi == 0 ? 2 : 0); st < 3; st++) {
                    const uint32_t tag = (ubase + 2 * gi + st) % 15u + 1u, tagp = (ubase + 2 * gi + st + 14u) % 15u + 1u;
                    if (st == 0) {
                        for (int b = bb0; b < bb0 + nb; b++) {
                            const int ctx = (gi == 3 ? 2 : 0) + b;
                            if (ctx == 3) { mbar_wait_long(bars + (BAR_PRE + 3) * 8); reset_words(); }
                            mbar_wait(bars + (BAR_CTX + ctx) * 8, 0);
                            const uint32_t pa = sb + SM_PART + (ctx & 1) * 3 * 528;
                            const float m0 = ldsf(pa + 512), m1 = ldsf(pa + 528 + 512), m2 = ldsf(pa + 1056 + 512);
                            const float M = fmaxf(m0, fmaxf(m1, m2));
                            const float Mt = ll_val(__float_as_uint(M));
                            const float f0 = ex2(m0 - Mt), f1 = ex2(m1 - Mt), f2 = ex2(m2 - Mt);
                            uint32_t* dst = g_opart[ctx][cta];
#pragma unroll
                            for (int i = 0; i < 4; i++) {
                                const uint32_t a = pa + (lane + 32 * i) * 4;
                                ll_store(dst + lane + 32 * i, ldsf(a) * f0 + ldsf(a + 528) * f1 + ldsf(a + 1056) * f2, tag0);
                            }
                            if (lane < 8) ll_store(dst + 128 + lane, lane ? ldsf(pa + 516) * f0 + ldsf(pa + 528 + 516) * f1 + ldsf(pa + 1056 + 516) * f2 : Mt, tag0);
                            TS(32 + gi * 16 + 0);
                        }
                        {
                            const uint32_t* src = g_opart[(gi == 3 ? 2 : 0) + bb0][4 * h];
                            uint32_t wm[8], wl[8], wo[8];
#pragma unroll
                            for (int i = 0; i < 8; i++) wm[i] = wl[i] = wo[i] = (i >= 4 && nb == 1) ? tag0 : 0u;
                            uint32_t it = 0;
                            while (true) {
#pragma unroll
                                for (int i = 0; i < 8; i++) {
                                    const uint32_t* q = src + (i >> 2) * (NCTA * 160) + (i & 3) * 160;
                                    ld_w2(q + 128, (((wm[i] ^ tag0) | (wl[i] ^ tag0)) & 15u) != 0, wm[i], wl[i]);
                                    ld_w1(q + 32 * j + lane, ((wo[i] ^ tag0) & 15u) != 0, wo[i]);
                                }
                                uint32_t miss = 0;
#pragma unroll
                                for (int i = 0; i < 8; i++) miss |= (wm[i] ^ tag0) | (wl[i] ^ tag0) | (wo[i] ^ tag0);
                                if (!__any_sync(0xffffffffu, (miss & 15u) != 0)) break;
                                SPIN_GUARD(it);
                            }
#pragma unroll
                            for (int bi = 0; bi < 2; bi++) {
                                if (bi < nb) {
                                    const float M = fmaxf(fmaxf(ll_val(wm[4 * bi]), ll_val(wm[4 * bi + 1])), fmaxf(ll_val(wm[4 * bi + 2]), ll_val(wm[4 * bi + 3])));
                                    float Ls = 0.f, O = 0.f;
#pragma unroll
                                    for (int i = 4 * bi; i < 4 * bi + 4; i++) { const float f = ex2(ll_val(wm[i]) - M); Ls += ll_val(wl[i]) * f; O += ll_val(wo[i]) * f; }
                                    sts16(sb + SM_V + bi * 80 + lane * 2, pack_bf16(O / Ls, 0.f));
                                }
                            }
                        }
                        __syncwarp();
                        uint32_t bx[4];
                        ldsm4(bx, vb);
                        TS(32 + gi * 16 + 1);
                        W.wait3();
                        {
                            uint32_t f[2][8][4];
                            frag8(f[0], W.a[0] + aoff);
#pragma unroll
                            for (int hs = 0; hs < 8; hs++) {
                                if (hs == 5) W.wait4();
                                if (hs < 7) frag8(f[(hs + 1) & 1], W.a[((hs + 1) >> 1) % 3] + aoff + ((hs + 1) & 1) * 4096);
                                float acc[4][4];
#pragma unroll
                                for (int u = 0; u < 4; u++) {
                                    acc[u][0] = acc[u][1] = acc[u][2] = acc[u][3] = 0.f;
                                    mma16816(acc[u], f[hs & 1][u], bx[0], bx[1]);
                                }
#pragma unroll
                                for (int u = 0; u < 4; u++) mma16816(acc[u], f[hs & 1][4 + u], bx[2], bx[3]);
                                if (hs == 1) load_fourth<0>(p, W, pol);
                                float o[4];
                                pick4(o, acc[0], acc[1], acc[2], acc[3], L.t);
                                uint32_t* d = outbox + hs * 4 * NCTA * 16;
                                ll_store(d, o[0], tag); ll_store(d + 8, o[2], tag);
                                if (nb == 2) { ll_store(d + OB, o[1], tag); ll_store(d + OB + 8, o[3], tag); }
                            }
                        }
                        W.rotate();
                        TS(32 + gi * 16 + 2);
                        if (!owner) load_stage<1, true>(p, W, pol);
                        if (gi == 3) fill_ones(sb, lane);
                    } else {
                        float s1[2] = {0.f, 0.f}, s2[2] = {0.f, 0.f};
                        if (gi) W.wait3();
                        if (gi == 0) {
                            float x[2][16];
#pragma unroll
                            for (int i = 0; i < 8; i++) {
                                uint32_t v[2];
                                asm volatile("ld.shared.v2.u32 {%0,%1}, [%2];" : "=r"(v[0]), "=r"(v[1]) : "r"(xnb + (i >> 2) * XS + (128 * (i & 3) + 4 * lane) * 2) : "memory");
                                float* xx = &x[i >> 2][4 * (i & 3)];
                                xx[0] = bf_lo(v[0]); xx[1] = bf_hi(v[0]); xx[2] = bf_lo(v[1]); xx[3] = bf_hi(v[1]);
                            }
                            ln_store2(x, xnb, lane);
                            W.wait3();
                        } else if (st == 2 || cta < NMLP) {
                            uint32_t w[8][4];
                            ll_gather<8, 128, 8 * 1024>(g_xrow[bb0][cta % XR] + 4 * lane, 4 * nb, tagp, w);
                            TS(32 + gi * 16 + 7 + st);
#pragma unroll
                            for (int i = 0; i < 8; i++)
                                if (i < 4 || nb == 2)
                                    sts64(xnb + (i >> 2) * XS + (128 * (i & 3) + 4 * lane) * 2, __byte_perm(w[i][0], w[i][1], 0x7632), __byte_perm(w[i][2], w[i][3], 0x7632));
#pragma unroll
                            for (int b = 0; b < 2; b++) {
                                float u[4], v[4];
#pragma unroll
                                for (int i = 0; i < 4; i++) {
                                    const float x0 = ll_val(w[4 * b + i][0]), x1 = ll_val(w[4 * b + i][1]), x2 = ll_val(w[4 * b + i][2]), x3 = ll_val(w[4 * b + i][3]);
                                    u[i] = (x0 + x1) + (x2 + x3);
                                    v[i] = (x0 * x0 + x1 * x1) + (x2 * x2 + x3 * x3);
                                }
                                s1[b] = (u[0] + u[1]) + (u[2] + u[3]); s2[b] = (v[0] + v[1]) + (v[2] + v[3]);
                            }
                        }
                        __syncwarp();
                        auto row_stats = [&]() {
#pragma unroll
                            for (int o = 16; o > 0; o >>= 1) {
                                s1[0] += __shfl_xor_sync(0xffffffffu, s1[0], o); s2[0] += __shfl_xor_sync(0xffffffffu, s2[0], o);
                                s1[1] += __shfl_xor_sync(0xffffffffu, s1[1], o); s2[1] += __shfl_xor_sync(0xffffffffu, s2[1], o);
                            }
#pragma unroll
                            for (int b = 0; b < 2; b++) {
                                s1[b] *= (1.f / DM);
                                s2[b] = rsqrtf(fmaxf(s2[b] * (1.f / DM) - s1[b] * s1[b], 0.f) + 1e-5f);
                            }
                        };
                        if (st == 1) TS(32 + gi * 16 + 4);
                        if (st == 2) {
                            float acc[8][4];
#pragma unroll
                            for (int u = 0; u < 8; u++) acc[u][0] = acc[u][1] = acc[u][2] = acc[u][3] = 0.f;
                            TS(32 + gi * 16 + 10);
                            {
                                uint32_t f[2][8][4], bx[4][4];
#pragma unroll
                                for (int it = 0; it < 4; it++) ldsm4(bx[it], xb + (128 * j + 32 * it) * 2);
                                frag8(f[0], W.a[0] + aoff);
#pragma unroll
                                for (int hs = 0; hs < 8; hs++) {
                                    if (hs == 5) W.wait4();
                                    if (hs < 7) frag8(f[(hs + 1) & 1], W.a[((hs + 1) >> 1) % 3] + aoff + ((hs + 1) & 1) * 4096);
#pragma unroll
                                    for (int u = 0; u < 4; u++) mma16816(acc[4 * (hs & 1) + u], f[hs & 1][u], bx[hs >> 1][0], bx[hs >> 1][1]);
#pragma unroll
                                    for (int u = 0; u < 4; u++) mma16816(acc[4 * (hs & 1) + u], f[hs & 1][4 + u], bx[hs >> 1][2], bx[hs >> 1][3]);
                                    if (hs == 1) load_fourth<2>(p, W, pol);
                                    if (hs == 2) row_stats();
                                }
                            }
                            W.rotate();
#pragma unroll
                            for (int q = 0; q < 2; q++) {
                                float o[4];
                                pick4(o, acc[4 * q], acc[4 * q + 1], acc[4 * q + 2], acc[4 * q + 3], L.t);
                                uint32_t* d = qout + 64 * q;
                                if (nb == 1) { o[0] = (o[0] - s1[0] * o[1]) * s2[0]; o[2] = (o[2] - s1[0] * o[3]) * s2[0]; }
                                ll_store(d, o[0], tag0); ll_store(d + 8, o[2], tag0);
                                if (nb == 2) { ll_store(d + NCTA * 128, o[1], tag0); ll_store(d + NCTA * 128 + 8, o[3], tag0); }
                            }
                            TS(32 + gi * 16 + 11);
                            break;
                        }
                        TS(32 + gi * 16 + 12);
                        if (cta < NMLP) {
                            float hh[4][4];
#pragma unroll
                            for (int u = 0; u < 4; u++) hh[u][0] = hh[u][1] = hh[u][2] = hh[u][3] = 0.f;
                            const uint32_t o1 = L.vrow * 32 + ((((lane >> 3) ^ (lane >> 2)) & 1) << 4);
                            uint32_t a[2][4][4], bq[2][2][4];
                            auto ld4 = [&](int s, int buf) {
                                const uint32_t wa = W.a[s >> 2] + o1 + (s & 3) * 2048;
                                ldsm4(bq[buf][0], xb + 128 * s); ldsm4(bq[buf][1], xb + 128 * s + 64);
#pragma unroll
                                for (int u = 0; u < 4; u++) ldsm4t(a[buf][u], wa + u * 512);
                            };
                            ld4(0, 0);
#pragma unroll
                            for (int s = 0; s < 8; s++) {
                                if (s < 7) ld4(s + 1, (s + 1) & 1);
#pragma unroll
                                for (int u = 0; u < 4; u++) mma16816(hh[u], a[s & 1][u], bq[s & 1][u >> 1][2 * (u & 1)], bq[s & 1][u >> 1][2 * (u & 1) + 1]);
                                if (s == 1) row_stats();
                                if (s == 3) load_fourth<1>(p, W, pol);
                            }
                            uint32_t f[2][8][4];
                            frag8(f[0], W.a[2] + aoff);
                            float hs4[4];
#pragma unroll
                            for (int i = 0; i < 4; i++) hs4[i] = (hh[0][i] + hh[1][i]) + (hh[2][i] + hh[3][i]);
                            float hv = (L.t & 2) ? hs4[2] : hs4[0], sw = (L.t & 2) ? hs4[3] : hs4[1];
                            const bool sec = nb == 2 && (L.t & 1);
                            if (nb == 2) {
                                const float r = __shfl_xor_sync(0xffffffffu, sw, 1);
                                if (L.t & 1) { sw = hv; hv = r; } else sw = r;
                            }
                            hv = (hv - (sec ? s1[1] : s1[0]) * sw) * (sec ? s2[1] : s2[0]);
                            sts16(sb + SM_V + (L.t & 1) * 80 + (L.g + 4 * (L.t & 2)) * 2, pack_bf16(gelu_tanh(bfr(bfr(hv) + bias)), 0.f));
                            __syncwarp();
                            uint32_t bx[4];
                            ldsm4(bx, vb);
#pragma unroll
                            for (int hs = 0; hs < 4; hs++) {
                                if (hs == 1) W.wait4();
                                if (hs < 3) frag8(f[(hs + 1) & 1], W.a[hs == 0 ? 2 : 0] + aoff + ((hs + 1) & 1) * 4096);
                                float acc[8][4];
#pragma unroll
                                for (int u = 0; u < 8; u++) {
                                    acc[u][0] = acc[u][1] = acc[u][2] = acc[u][3] = 0.f;
                                    mma16816(acc[u], f[hs & 1][u], bx[0], bx[1]);
                                }
#pragma unroll
                                for (int qq = 0; qq < 2; qq++) {
                                    float o[4];
                                    pick4(o, acc[4 * qq], acc[4 * qq + 1], acc[4 * qq + 2], acc[4 * qq + 3], L.t);
                                    uint32_t* d = outbox + (hs * 8 + qq * 4) * NCTA * 16;
                                    ll_store(d, o[0], tag); ll_store(d + 8, o[2], tag);
                                    if (nb == 2) { ll_store(d + OB, o[1], tag); ll_store(d + OB + 8, o[3], tag); }
                                }
                            }
                        }
                        W.rotate();
                        TS(32 + gi * 16 + 5);
                        if (!owner && gi < 3) load_stage<2, true>(p, W, pol);
                    }
                    if (owner) {
                        uint32_t w[16][4];
                        ll_gather<16, 128, 0>(&g_inbox[ob][oo][0][0] + 4 * lane, st == 0 ? 16 : NMLP / 8, tag, w);
                        uint32_t xw[4];
#pragma unroll
                        for (int e = 0; e < 4; e++) {
                            float c[4];
#pragma unroll
                            for (int i = 0; i < 4; i++) c[i] = (ll_val(w[i][e]) + ll_val(w[4 + i][e])) + (ll_val(w[8 + i][e]) + ll_val(w[12 + i][e]));
                            float t = (c[0] + c[1]) + (c[2] + c[3]);
                            t += __shfl_xor_sync(0xffffffffu, t, 4); t += __shfl_xor_sync(0xffffffffu, t, 8); t += __shfl_xor_sync(0xffffffffu, t, 16);
                            xown[e] = bfr(xown[e] + (st == 0 ? bfr(t) : bfr(bfr(t) + b2own[e])));
                            xw[e] = __float_as_uint(xown[e]) | tag;
                        }
                        if (gi == 3 && st == 1) {
                            if (lane < 4) *reinterpret_cast<uint2*>(p.out + ob * DM + 16 * oo + 4 * lane) = make_uint2(pack_bf16(xown[0], xown[1]), pack_bf16(xown[2], xown[3]));
                        } else if (lane < 4 * XR) st_w4(xout, xw[0], xw[1], xw[2], xw[3]);
                    }
                    TS(32 + gi * 16 + 3 + 3 * st);
                    if (gi == 3 && st == 1) break;
                    if (owner) { if (st == 0) load_stage<1, true>(p, W, pol); else load_stage<2, true>(p, W, pol); }
                }
                if (gi == 3) break;
                {
                    uint32_t w[8][4];
                    ll_gather<8, 128, NCTA * 128>(g_qpart[(gi ? 2 : 0) + bb0][4 * h] + 4 * lane, 4 * nb, tag0, w);
#pragma unroll
                    for (int bi = 0; bi < 2; bi++) {
                        if (bi < nb) {
                            float q[4];
#pragma unroll
                            for (int e = 0; e < 4; e++) q[e] = (ll_val(w[4 * bi][e]) + ll_val(w[4 * bi + 1][e])) + (ll_val(w[4 * bi + 2][e]) + ll_val(w[4 * bi + 3][e]));
                            const uint32_t w0 = pack_bf16(q[0], q[1]), w1 = pack_bf16(q[2], q[3]);
                            const int ch = lane >> 1;
#pragma unroll
                            for (int kp = 0; kp < 4; kp++) {
                                const int jj = ch ^ kp;
#pragma unroll
                                for (int e = 0; e < 2; e++) {
                                    const int row = 4 * kp + 2 * (lane & 1) + e;
                                    sts32(sb + SM_Q + (bb0 + bi) * 1024 + row * 64 + (((jj >> 2) ^ ((row >> 1) & 3)) << 4) + (jj & 3) * 4, e ? w1 : w0);
                                }
                            }
                        }
                    }
                    __syncwarp();
                    if (lane < nb) mbar_arrive(bars + (BAR_Q + (gi ? 2 : 0) + bb0 + lane) * 8);
                }
                TS(32 + gi * 16 + 7);
                load_stage<0, false>(p, W, pol);
                if (gi == 0) fill_ones(xnb + XS, lane);
            }
            if (lane == 0) TSYNC(1);
            if (cta == NCTA - 1 && lane == 0) asm volatile("st.relaxed.gpu.global.u32 [%0], %1;" ::"l"(&g_epoch), "r"(epoch + 1) : "memory");
        }
    }
}

typedef CUresult (*EncodeFn)(CUtensorMap*, CUtensorMapDataType, cuuint32_t, void*, const cuuint64_t*, const cuuint64_t*, const cuuint32_t*,
                             const cuuint32_t*, CUtensorMapInterleave, CUtensorMapSwizzle, CUtensorMapL2promotion, CUtensorMapFloatOOBfill);
void encode2d(EncodeFn fn, CUtensorMap* m, void* base, uint64_t cols, uint64_t rows, uint32_t bcols, uint32_t brows, CUtensorMapSwizzle sw) {
    const cuuint64_t dim[2] = {cols, rows}, stride[1] = {cols * 2};
    const cuuint32_t box[2] = {bcols, brows}, es[2] = {1, 1};
    fn(m, CU_TENSOR_MAP_DATA_TYPE_BFLOAT16, 2, base, dim, stride, box, es, CU_TENSOR_MAP_INTERLEAVE_NONE, sw,
       CU_TENSOR_MAP_L2_PROMOTION_L2_128B, CU_TENSOR_MAP_FLOAT_OOB_FILL_NONE);
}

}

extern "C" void kernel_launch(void* const* d_in, const int* in_sizes, int n_in, void* d_out, int out_size) {
    (void)in_sizes; (void)n_in; (void)out_size;
    static EncodeFn enc = nullptr;
    if (!enc) {
        cudaFuncSetAttribute(fused_kernel, cudaFuncAttributeMaxDynamicSharedMemorySize, (int)SM_TOTAL);
        void* fn = nullptr;
        cudaDriverEntryPointQueryResult qr;
        cudaGetDriverEntryPoint("cuTensorMapEncodeTiled", &fn, cudaEnableDefault, &qr);
        enc = (EncodeFn)fn;
    }
    Params p;
    encode2d(enc, &p.mwq, d_in[3], HD, DM, 64, 32, CU_TENSOR_MAP_SWIZZLE_128B);
    encode2d(enc, &p.mwo, d_in[4], DM, HD, 64, 32, CU_TENSOR_MAP_SWIZZLE_128B);
    encode2d(enc, &p.mw1, d_in[6], FF, DM, 16, 256, CU_TENSOR_MAP_SWIZZLE_32B);
    encode2d(enc, &p.mw2, d_in[8], DM, FF, 64, 16, CU_TENSOR_MAP_SWIZZLE_128B);
    p.x = (const __nv_bfloat16*)d_in[0];
    p.k = (const __nv_bfloat16*)d_in[1];
    p.v = (const __nv_bfloat16*)d_in[2];
    p.b1 = (const __nv_bfloat16*)d_in[7];
    p.b2 = (const __nv_bfloat16*)d_in[9];
    p.out = (__nv_bfloat16*)d_out;
    fused_kernel<<<NCTA, 384, SM_TOTAL>>>(p);
}
```

```cpp
#include <cuda_runtime.h>
#include <cuda.h>
#include <cuda_bf16.h>
#include <stdint.h>

namespace {

constexpr int NCTA = 128;
constexpr int DM = 512, FF = 1792, HD = 4096;
constexpr int NMLP = 112;
constexpr uint32_t HALF_B = 8192;
constexpr uint32_t SLOT_B = 16384;
constexpr int NT = 64;

#define P_NRF 11
#define P_NL2 21
#define P_REG_LO 120
#define P_REG_HI 192
constexpr int PRE = 2;
constexpr int MIX = 1;
constexpr int NSB = 3;
constexpr int NB = 3 * NSB, NSLOT = 3 + NB;
constexpr int NRF = P_NRF;
constexpr int NL2 = P_NL2;
constexpr int NNR = NT - NB - NRF - NL2;
constexpr int TB = NT - NB;
constexpr int NZ = NRF + NL2;

constexpr int BAR_FULL = 0;
constexpr int BAR_RF = NSLOT, BAR_CAP = BAR_RF + 2 * NRF, BAR_FREE = BAR_CAP + 2 * NRF, BAR_DUMP = BAR_FREE + 2 * NRF;
constexpr int BAR_Q = BAR_DUMP + 2 * NRF, BAR_CTX = BAR_Q + 4, BAR_TAB = BAR_CTX + 4, BAR_W = BAR_TAB + 1, BAR_PRE = BAR_W + 2, NBAR = BAR_PRE + 4;

enum { F_NONE = 0, F_TILE = 1, F_KEEP = 2, F_FREE = 4 };
constexpr uint32_t D_NOPROC = 1u << 12, D_FLUSH = 1u << 13, D_PRE = 1u << 21, D_END = 1u << 31;
struct Desc { uint32_t w0, w1; };
constexpr int LA = 66, LB = 42;
struct Tables {
    Desc a[3][LA];
    Desc b[3][LB];
    uint32_t inita[4];
    int capslot[2][NRF], dumpslot[2][NRF];
    bool ok;
};
enum { K_TILE = 0, K_CAP = 1, K_L2 = 2, K_DUMP = 4, K_RES = 5 };
struct Item { int kind, ctx, idx; };
constexpr uint32_t mk0(int bar, int par, int ctx, int slot) { return (uint32_t)(bar * 8) | ((uint32_t)par << 11) | ((uint32_t)ctx << 14) | ((uint32_t)slot << 16); }
constexpr uint32_t mkfill(const Item& x, int slot) {
    const int b = x.ctx & 1;
    if (x.kind == K_DUMP) return F_FREE | ((uint32_t)((BAR_FREE + b * NRF + x.idx - NNR) * 8) << 4);
    if (x.kind == K_RES) return F_NONE;
    const int bar = x.kind == K_CAP ? BAR_RF + b * NRF + x.idx - NNR : BAR_FULL + slot;
    return (x.kind == K_L2 ? F_KEEP : F_TILE) | ((uint32_t)(bar * 8) << 4) | ((uint32_t)(b * 8192 + x.idx) << 16);
}
constexpr Tables build_tables() {
    Tables T{};
    T.ok = true;
    Item A[256] = {};
    int n = 0;
    auto tiles = [&](int kind, int ctx, int lo, int hi) { for (int i = lo; i < hi; i++) A[n++] = Item{kind, ctx, i}; };
    for (int c = 0; c < 2; c++) { tiles(K_TILE, c, 0, NNR); tiles(K_CAP, c, NNR, NNR + NRF); tiles(K_L2, c, NNR + NRF, TB); }
    tiles(K_TILE, 2, 0, NNR);
    tiles(K_TILE, 3, 0, NNR);
    const int NA = n;
    for (int w = 0; w < 3; w++) {
        int m = 0, par = 0, cur = -1;
        T.inita[w] = mkfill(A[w], w);
        for (int i = w; i < NA; i += 3) {
            const Item x = A[i];
            const uint32_t fill = i + 3 < NA ? mkfill(A[i + 3], w) : (uint32_t)F_NONE;
            if (x.ctx != cur) T.a[w][m++] = Desc{mk0(BAR_Q + x.ctx, 0, 0, w) | D_NOPROC, F_NONE};
            cur = x.ctx;
            int left = 0;
            for (int k = i + 3; k < NA; k += 3) if (A[k].ctx == cur) left++;
            const uint32_t fl = (left == 0 ? D_FLUSH : 0u) | (cur != 2 && w == 0 && left == PRE ? D_PRE : 0u);
            const int b = x.ctx & 1;
            if (x.kind == K_CAP) {
                T.capslot[b][x.idx - NNR] = w;
                T.a[w][m++] = Desc{mk0(BAR_RF + b * NRF + x.idx - NNR, 0, x.ctx, w) | fl, F_NONE};
                T.a[w][m++] = Desc{mk0(BAR_CAP + b * NRF + x.idx - NNR, 0, 0, w) | D_NOPROC, fill};
            } else {
                T.a[w][m++] = Desc{mk0(BAR_FULL + w, par, x.ctx, w) | fl, fill};
                par ^= 1;
            }
        }
        T.a[w][m++] = Desc{D_END, F_NONE};
        if (m > LA) T.ok = false;
        const int s0 = 3 + NSB * w;
        Item B[64] = {};
        int nb = 0;
        for (int h = 0; h < 2; h++) {
            for (int k = 0; k < NSB; k++) B[nb++] = Item{K_TILE, h, TB + s0 - 3 + k};
            for (int k = 0; k < NSB; k++) B[nb++] = Item{K_RES, 2 + h, 0};
            int zd = w, zl = NRF + (w + 3 - NRF % 3) % 3;
            while (zd < NRF || zl < NZ) {
                if (zd < NRF) { B[nb++] = Item{K_DUMP, 2 + h, NNR + zd}; zd += 3; }
                for (int k = 0; (k < MIX || zd >= NRF) && zl < NZ; k++) { B[nb++] = Item{K_TILE, 2 + h, NNR + zl}; zl += 3; }
            }
        }
        m = 0;
        int parb[NSB] = {};
        for (int k = 0; k < NSB; k++) T.b[w][m++] = Desc{mk0(BAR_FULL + (k ? s0 + k - 1 : w), 0, 0, s0 + k) | D_NOPROC, mkfill(B[k], s0 + k)};
        cur = -1;
        for (int i = 0; i < nb; i++) {
            const Item x = B[i];
            const int k = i % NSB, slot = s0 + k;
            const uint32_t fill = i + NSB < nb ? mkfill(B[i + NSB], slot) : (uint32_t)F_NONE;
            if (x.ctx != cur && x.kind != K_RES) T.b[w][m++] = Desc{mk0(BAR_Q + x.ctx, 0, 0, slot) | D_NOPROC, F_NONE};
            cur = x.ctx;
            const uint32_t fl = (i + 1 == nb || B[i + 1].ctx != cur) ? D_FLUSH : 0u;
            const int b = x.ctx & 1;
            if (x.kind == K_RES) T.b[w][m++] = Desc{mk0(BAR_Q + x.ctx, 0, x.ctx, slot) | fl, fill};
            else if (x.kind == K_DUMP) {
                T.dumpslot[b][x.idx - NNR] = slot;
                T.b[w][m++] = Desc{mk0(BAR_DUMP + b * NRF + x.idx - NNR, 0, x.ctx, slot) | fl, fill};
            } else { T.b[w][m++] = Desc{mk0(BAR_FULL + slot, parb[k], x.ctx, slot) | fl, fill}; parb[k] ^= 1; }
        }
        T.b[w][m++] = Desc{D_END, F_NONE};
        if (m > LB) T.ok = false;
    }
    return T;
}
constexpr Tables HT = build_tables();
static_assert(HT.ok, "schedule does not fit");
constexpr unsigned long long pack_slots(const int* v) { unsigned long long r = 0; for (int i = 0; i < NRF; i++) r |= (unsigned long long)v[i] << (4 * i); return r; }
constexpr unsigned long long CAP0 = pack_slots(HT.capslot[0]), CAP1 = pack_slots(HT.capslot[1]);
constexpr unsigned long long DUMP0 = pack_slots(HT.dumpslot[0]), DUMP1 = pack_slots(HT.dumpslot[1]);
constexpr uint32_t INITA0 = HT.inita[0], INITA1 = HT.inita[1], INITA2 = HT.inita[2];
static_assert(NRF <= 16, "slot packing");
__device__ const Tables g_tab = build_tables();
constexpr uint32_t TAB_BYTES = (3 * LA + 3 * LB) * 8;
static_assert(TAB_BYTES % 16 == 0, "bulk copy size");

constexpr uint32_t SM_W = NSLOT * SLOT_B;
constexpr uint32_t SM_Q = SM_W + 3 * 8192;
constexpr uint32_t SM_PART = SM_Q + 2048;
constexpr uint32_t XS = 1040;
constexpr uint32_t SM_XN = SM_PART + 6 * 528;
constexpr uint32_t SM_BIAS = SM_XN + 2 * XS;
constexpr uint32_t SM_V = SM_BIAS + 64;
constexpr uint32_t SM_XO = SM_V + 80;
constexpr uint32_t SM_EPOCH = SM_XO + 64;
constexpr uint32_t SM_TAB = SM_XO + 80;
constexpr uint32_t SM_BAR = SM_TAB + TAB_BYTES;
constexpr uint32_t SM_TOTAL = SM_BAR + NBAR * 8;
static_assert(SM_TOTAL <= 232448 && NBAR * 8 < 2048, "shared memory budget");

constexpr int XR = 8;
__device__ __align__(128) uint32_t g_opart[4][NCTA][160];
__device__ __align__(128) uint32_t g_qpart[4][NCTA][128];
__device__ __align__(128) uint32_t g_inbox[2][32][NCTA][16];
__device__ __align__(128) uint32_t g_xrow[4][8][1024];
__device__ unsigned g_epoch;
#define TS(i) do {} while (0)
#define TSYNC(k) do {} while (0)

struct Params {
    const __nv_bfloat16 *x, *k, *v, *b1, *b2;
    __nv_bfloat16* out;
    CUtensorMap mwq, mwo, mw1, mw2;
};

__device__ __forceinline__ void mbar_init(uint32_t bar, int cnt) { asm volatile("mbarrier.init.shared::cta.b64 [%0], %1;" ::"r"(bar), "r"(cnt)); }
__device__ __forceinline__ void mbar_expect_tx(uint32_t bar, uint32_t bytes) { asm volatile("mbarrier.arrive.expect_tx.shared::cta.b64 _, [%0], %1;" ::"r"(bar), "r"(bytes) : "memory"); }
__device__ __forceinline__ void mbar_arrive(uint32_t bar) { asm volatile("mbarrier.arrive.shared::cta.b64 _, [%0];" ::"r"(bar) : "memory"); }
__device__ __forceinline__ bool mbar_test(uint32_t bar, uint32_t parity) {
    uint32_t ok;
    asm volatile("{\n.reg .pred p;\nmbarrier.test_wait.parity.shared::cta.b64 p, [%1], %2;\nselp.u32 %0, 1, 0, p;\n}" : "=r"(ok) : "r"(bar), "r"(parity) : "memory");
    return ok;
}
__device__ __forceinline__ bool mbar_try(uint32_t bar, uint32_t parity) {
    uint32_t ok;
    asm volatile("{\n.reg .pred p;\nmbarrier.try_wait.parity.shared::cta.b64 p, [%1], %2;\nselp.u32 %0, 1, 0, p;\n}" : "=r"(ok) : "r"(bar), "r"(parity) : "memory");
    return ok;
}
__device__ __forceinline__ void mbar_wait(uint32_t bar, uint32_t parity) {
    uint32_t it = 0;
    while (!mbar_try(bar, parity)) { if (++it > (1u << 24)) __trap(); }
}
__device__ __forceinline__ void mbar_wait_long(uint32_t bar) {
    uint32_t it = 0, ok;
    do {
        asm volatile("{\n.reg .pred p;\nmbarrier.try_wait.parity.shared::cta.b64 p, [%1], 0, %2;\nselp.u32 %0, 1, 0, p;\n}" : "=r"(ok) : "r"(bar), "r"(2000u) : "memory");
        if (++it > (1u << 22)) __trap();
    } while (!ok);
}
__device__ __forceinline__ bool elect_one() {
    uint32_t r;
    asm volatile("{\n.reg .pred P;\nelect.sync _|P, 0xffffffff;\nselp.b32 %0, 1, 0, P;\n}" : "=r"(r));
    return r;
}
__device__ __forceinline__ bool mbar_test_warp(uint32_t bar, uint32_t parity) { return __all_sync(0xffffffffu, mbar_test(bar, parity)); }
__device__ __forceinline__ void bulk_g2s(uint32_t dst, const void* src, uint32_t bytes, uint32_t bar, uint64_t pol) {
    asm volatile("cp.async.bulk.shared::cluster.global.mbarrier::complete_tx::bytes.L2::cache_hint [%0], [%1], %2, [%3], %4;"
                 ::"r"(dst), "l"(src), "r"(bytes), "r"(bar), "l"(pol) : "memory");
}
__device__ __forceinline__ void bulk_prefetch(const void* src, uint32_t bytes) {
    asm volatile("cp.async.bulk.prefetch.L2.global [%0], %1;" ::"l"(src), "r"(bytes) : "memory");
}
__device__ __forceinline__ void half_fill(bool cond, bool arm, bool keep, uint32_t dst, const void* src, uint32_t bar, uint64_t pol) {
    asm volatile("{\n.reg .pred e, a, k;\nelect.sync _|e, 0xffffffff;\nsetp.ne.and.u32 e, %0, 0, e;\nsetp.ne.and.u32 a, %1, 0, e;\nsetp.ne.and.u32 k, %2, 0, e;\n"
                 "@a mbarrier.arrive.expect_tx.shared::cta.b64 _, [%5], 16384;\n"
                 "@e cp.async.bulk.shared::cluster.global.mbarrier::complete_tx::bytes.L2::cache_hint [%3], [%4], 8192, [%5], %6;\n"
                 "@k cp.async.bulk.prefetch.L2.global [%4], 8192;\n}"
                 ::"r"((uint32_t)cond), "r"((uint32_t)arm), "r"((uint32_t)keep), "r"(dst), "l"(src), "r"(bar), "l"(pol) : "memory");
}
__device__ __forceinline__ void ldsm4(uint32_t (&r)[4], uint32_t a) {
    asm volatile("ldmatrix.sync.aligned.m8n8.x4.shared.b16 {%0,%1,%2,%3}, [%4];" : "=r"(r[0]), "=r"(r[1]), "=r"(r[2]), "=r"(r[3]) : "r"(a));
}
__device__ __forceinline__ void ldsm4t(uint32_t (&r)[4], uint32_t a) {
    asm volatile("ldmatrix.sync.aligned.m8n8.x4.trans.shared.b16 {%0,%1,%2,%3}, [%4];" : "=r"(r[0]), "=r"(r[1]), "=r"(r[2]), "=r"(r[3]) : "r"(a));
}
__device__ __forceinline__ void mma16816(float (&c)[4], const uint32_t (&a)[4], uint32_t b0, uint32_t b1) {
    asm volatile("mma.sync.aligned.m16n8k16.row.col.f32.bf16.bf16.f32 {%0,%1,%2,%3}, {%4,%5,%6,%7}, {%8,%9}, {%0,%1,%2,%3};"
                 : "+f"(c[0]), "+f"(c[1]), "+f"(c[2]), "+f"(c[3]) : "r"(a[0]), "r"(a[1]), "r"(a[2]), "r"(a[3]), "r"(b0), "r"(b1));
}
__device__ __forceinline__ void lds128(uint32_t* r, uint32_t a) {
    asm volatile("ld.shared.v4.u32 {%0,%1,%2,%3}, [%4];" : "=r"(r[0]), "=r"(r[1]), "=r"(r[2]), "=r"(r[3]) : "r"(a) : "memory");
}
__device__ __forceinline__ void sts128(uint32_t a, const uint32_t* r) {
    asm volatile("st.shared.v4.u32 [%0], {%1,%2,%3,%4};" ::"r"(a), "r"(r[0]), "r"(r[1]), "r"(r[2]), "r"(r[3]) : "memory");
}
__device__ __forceinline__ uint32_t lds32(uint32_t a) { uint32_t r; asm volatile("ld.shared.u32 %0, [%1];" : "=r"(r) : "r"(a) : "memory"); return r; }
__device__ __forceinline__ uint32_t lds16(uint32_t a) { uint16_t r; asm volatile("ld.shared.u16 %0, [%1];" : "=h"(r) : "r"(a) : "memory"); return r; }
__device__ __forceinline__ float ldsf(uint32_t a) { float r; asm volatile("ld.shared.f32 %0, [%1];" : "=f"(r) : "r"(a) : "memory"); return r; }
__device__ __forceinline__ void sts32(uint32_t a, uint32_t v) { asm volatile("st.shared.u32 [%0], %1;" ::"r"(a), "r"(v) : "memory"); }
__device__ __forceinline__ void sts16(uint32_t a, uint32_t v) { asm volatile("st.shared.u16 [%0], %1;" ::"r"(a), "h"((uint16_t)v) : "memory"); }
__device__ __forceinline__ void stsf(uint32_t a, float v) { asm volatile("st.shared.f32 [%0], %1;" ::"r"(a), "f"(v) : "memory"); }
__device__ __forceinline__ void sts64(uint32_t a, uint32_t v0, uint32_t v1) { asm volatile("st.shared.v2.u32 [%0], {%1,%2};" ::"r"(a), "r"(v0), "r"(v1) : "memory"); }
__device__ __forceinline__ void cp16(uint32_t dst, const void* src) { asm volatile("cp.async.cg.shared.global [%0], [%1], 16;" ::"r"(dst), "l"(src) : "memory"); }
__device__ __forceinline__ float ex2(float x) { float r; asm("ex2.approx.ftz.f32 %0, %1;" : "=f"(r) : "f"(x)); return r; }
__device__ __forceinline__ uint32_t pack_bf16(float lo, float hi) { uint32_t r; asm("cvt.rn.bf16x2.f32 %0, %1, %2;" : "=r"(r) : "f"(hi), "f"(lo)); return r; }
__device__ __forceinline__ float bf_lo(uint32_t v) { return __uint_as_float(v << 16); }
__device__ __forceinline__ float bf_hi(uint32_t v) { return __uint_as_float(v & 0xffff0000u); }
__device__ __forceinline__ float bfr(float x) { return __bfloat162float(__float2bfloat16_rn(x)); }
__device__ __forceinline__ uint32_t ll_pack(float v, uint32_t tag) { return (__float_as_uint(v) & ~15u) | tag; }
__device__ __forceinline__ float ll_val(uint32_t w) { return __uint_as_float(w & ~15u); }
__device__ __forceinline__ void st_w(uint32_t* p, uint32_t w) { asm volatile("st.relaxed.gpu.global.u32 [%0], %1;" ::"l"(p), "r"(w) : "memory"); }
__device__ __forceinline__ void st_w4(uint32_t* p, uint32_t a, uint32_t b, uint32_t c, uint32_t d) {
    asm volatile("st.relaxed.gpu.global.v4.u32 [%0], {%1,%2,%3,%4};" ::"l"(p), "r"(a), "r"(b), "r"(c), "r"(d) : "memory");
}
__device__ __forceinline__ void ll_store(uint32_t* p, float v, uint32_t tag) { st_w(p, ll_pack(v, tag)); }
__device__ __forceinline__ void ld_w4(const uint32_t* p, bool pred, uint32_t (&w)[4]) {
    asm volatile("{\n.reg .pred q;\nsetp.ne.u32 q, %5, 0;\n@q ld.relaxed.gpu.global.v4.u32 {%0,%1,%2,%3}, [%4];\n}"
                 : "+r"(w[0]), "+r"(w[1]), "+r"(w[2]), "+r"(w[3]) : "l"(p), "r"((uint32_t)pred) : "memory");
}
__device__ __forceinline__ void ld_w2(const uint32_t* p, bool pred, uint32_t& a, uint32_t& b) {
    asm volatile("{\n.reg .pred q;\nsetp.ne.u32 q, %3, 0;\n@q ld.relaxed.gpu.global.v2.u32 {%0,%1}, [%2];\n}" : "+r"(a), "+r"(b) : "l"(p), "r"((uint32_t)pred) : "memory");
}
__device__ __forceinline__ void ld_w1(const uint32_t* p, bool pred, uint32_t& a) {
    asm volatile("{\n.reg .pred q;\nsetp.ne.u32 q, %2, 0;\n@q ld.relaxed.gpu.global.u32 %0, [%1];\n}" : "+r"(a) : "l"(p), "r"((uint32_t)pred) : "memory");
}
__device__ __forceinline__ bool miss4(const uint32_t (&w)[4], uint32_t tag) { return (((w[0] ^ tag) | (w[1] ^ tag) | (w[2] ^ tag) | (w[3] ^ tag)) & 15u) != 0; }
#define SPIN_GUARD(it) do { if (++(it) > (1u << 22)) __trap(); } while (0)

struct PVB { uint32_t x0, x1, y0, y1; };
struct LaneC {
    int g, t, v;
    int src0, src1;
    uint32_t sx0, sy0;
    uint32_t voff;
    int vrow;
};
__device__ __forceinline__ PVB spread(uint32_t pk, const LaneC& L) {
    uint32_t v0 = __shfl_sync(0xffffffffu, pk, L.src0), v1 = __shfl_sync(0xffffffffu, pk, L.src1);
    PVB b;
    b.x0 = __byte_perm(v0, 0, L.sx0); b.y0 = __byte_perm(v0, 0, L.sy0);
    b.x1 = __byte_perm(v1, 0, L.sx0 ^ 0x5454u); b.y1 = __byte_perm(v1, 0, L.sy0 ^ 0x7676u);
    return b;
}
__device__ __forceinline__ void pv_load(uint32_t (&a)[8][4], uint32_t base) {
#pragma unroll
    for (int c = 0; c < 8; c++) ldsm4t(a[c], base ^ (c << 4));
}
template <int U> __device__ __forceinline__ void raw_load(uint32_t (&r)[16], uint32_t a) {
    asm volatile("ld.shared.v4.u32 {%0,%1,%2,%3}, [%16];\nld.shared.v4.u32 {%4,%5,%6,%7}, [%16+512];\n"
                 "ld.shared.v4.u32 {%8,%9,%10,%11}, [%16+1024];\nld.shared.v4.u32 {%12,%13,%14,%15}, [%16+1536];\nmembar.cta; // %17"
                 : "=r"(r[0]), "=r"(r[1]), "=r"(r[2]), "=r"(r[3]), "=r"(r[4]), "=r"(r[5]), "=r"(r[6]), "=r"(r[7]), "=r"(r[8]), "=r"(r[9]),
                   "=r"(r[10]), "=r"(r[11]), "=r"(r[12]), "=r"(r[13]), "=r"(r[14]), "=r"(r[15]) : "r"(a), "n"(U) : "memory");
}
template <int U> __device__ __forceinline__ void raw_store(const uint32_t (&r)[16], uint32_t a) {
    asm volatile("st.shared.v4.u32 [%16], {%0,%1,%2,%3};\nst.shared.v4.u32 [%16+512], {%4,%5,%6,%7};\n"
                 "st.shared.v4.u32 [%16+1024], {%8,%9,%10,%11};\nst.shared.v4.u32 [%16+1536], {%12,%13,%14,%15};\nfence.proxy.async.shared::cta; // %17"
                 :: "r"(r[0]), "r"(r[1]), "r"(r[2]), "r"(r[3]), "r"(r[4]), "r"(r[5]), "r"(r[6]), "r"(r[7]), "r"(r[8]), "r"(r[9]),
                    "r"(r[10]), "r"(r[11]), "r"(r[12]), "r"(r[13]), "r"(r[14]), "r"(r[15]), "r"(a), "n"(U) : "memory");
}
template <int LO, int HI, bool LOAD> __device__ __forceinline__ void raw_dispatch(uint32_t (&r)[NRF][16], int u, uint32_t a) {
    if constexpr (HI - LO == 1) {
        if constexpr (LOAD) raw_load<LO>(r[LO], a); else raw_store<LO>(r[LO], a);
    } else {
        constexpr int MID = (LO + HI) / 2;
        if (u < MID) raw_dispatch<LO, MID, LOAD>(r, u, a); else raw_dispatch<MID, HI, LOAD>(r, u, a);
    }
}

struct Ctx { float o[4]; float m, l; };
constexpr float SCL = 0.08838834764831845f * 1.4426950408889634f;

__device__ __forceinline__ void process_tile(Ctx& S, uint32_t tile, uint32_t qaddr, uint32_t koff, uint32_t voff, const LaneC& L,
                                             uint32_t fill, uint32_t bars, const Params& p, uint64_t pol) {
    float sa0[4] = {0.f, 0.f, 0.f, 0.f}, sa1[4] = {0.f, 0.f, 0.f, 0.f}, sb0[4] = {0.f, 0.f, 0.f, 0.f}, sb1[4] = {0.f, 0.f, 0.f, 0.f};
    const uint32_t kb = tile + koff;
    {
        uint32_t q[4][4], a[4][4][4];
#pragma unroll
        for (int i = 0; i < 4; i++) {
            lds128(q[i], qaddr ^ (i << 4));
            const uint32_t k0 = kb ^ ((2 * i) << 5), k1 = kb ^ ((2 * i + 1) << 5);
            ldsm4(a[i][0], k0); ldsm4(a[i][1], k1); ldsm4(a[i][2], k0 + 4096); ldsm4(a[i][3], k1 + 4096);
            if (i > 0) {
                mma16816(sa0, a[i - 1][0], q[i - 1][0], q[i - 1][1]); mma16816(sa1, a[i - 1][1], q[i - 1][2], q[i - 1][3]);
                mma16816(sb0, a[i - 1][2], q[i - 1][0], q[i - 1][1]); mma16816(sb1, a[i - 1][3], q[i - 1][2], q[i - 1][3]);
            }
        }
        mma16816(sa0, a[3][0], q[3][0], q[3][1]); mma16816(sa1, a[3][1], q[3][2], q[3][3]);
        mma16816(sb0, a[3][2], q[3][0], q[3][1]); mma16816(sb1, a[3][3], q[3][2], q[3][3]);
    }
    const uint32_t vb = tile + voff;
    uint32_t av[8][4];
    pv_load(av, vb);
    const bool refill = ((fill & 7) - 1u) < 2u;
    const uint32_t fbar = bars + ((fill >> 4) & 0x7ff);
    const size_t foff = ((size_t)blockIdx.x << 19) + ((fill >> 16) << 13);
    const char* kbase = reinterpret_cast<const char*>(p.k);
    const char* vbase = reinterpret_cast<const char*>(p.v);
    half_fill(refill, true, fill & 2, tile, kbase + foff, fbar, pol);
    const bool odd = L.g & 1;
    const bool valid = (L.v == 0);
    const float s0 = (odd ? sa0[1] + sa1[1] : sa0[0] + sa1[0]) * SCL, s1 = (odd ? sa0[3] + sa1[3] : sa0[2] + sa1[2]) * SCL;
    const float s2 = (odd ? sb0[1] + sb1[1] : sb0[0] + sb1[0]) * SCL, s3 = (odd ? sb0[3] + sb1[3] : sb0[2] + sb1[2]) * SCL;
    float mx = valid ? fmaxf(fmaxf(s0, s1), fmaxf(s2, s3)) : -INFINITY;
    if (__any_sync(0xffffffffu, mx > S.m)) {
#pragma unroll
        for (int o = 16; o > 0; o >>= 1) mx = fmaxf(mx, __shfl_xor_sync(0xffffffffu, mx, o));
        const float f = ex2(S.m - mx);
        S.o[0] *= f; S.o[1] *= f; S.o[2] *= f; S.o[3] *= f; S.l *= f;
        S.m = mx;
    }
    const float p0 = ex2(s0 - S.m), p1 = ex2(s1 - S.m), p2 = ex2(s2 - S.m), p3 = ex2(s3 - S.m);
    if (valid) S.l += (p0 + p1) + (p2 + p3);
    const PVB ba = spread(pack_bf16(p0, p1), L), bb = spread(pack_bf16(p2, p3), L);
    float o1[4] = {0.f, 0.f, 0.f, 0.f}, o2[4] = {0.f, 0.f, 0.f, 0.f}, o3[4] = {0.f, 0.f, 0.f, 0.f};
#pragma unroll
    for (int c = 0; c < 8; c += 2) {
        const bool on = (L.v == (c >> 1));
        uint32_t w0[4], w1[4];
        ldsm4t(w0, (vb ^ (c << 4)) + 4096); ldsm4t(w1, (vb ^ ((c + 1) << 4)) + 4096);
        mma16816(S.o, av[c], on ? ba.x0 : 0u, on ? ba.y0 : 0u);
        mma16816(o1, av[c + 1], on ? ba.x1 : 0u, on ? ba.y1 : 0u);
        mma16816(o2, w0, on ? bb.x0 : 0u, on ? bb.y0 : 0u);
        mma16816(o3, w1, on ? bb.x1 : 0u, on ? bb.y1 : 0u);
    }
    half_fill(refill, false, fill & 2, tile + HALF_B, vbase + foff, fbar, pol);
    S.o[0] += o1[0] + (o2[0] + o3[0]); S.o[1] += o1[1] + (o2[1] + o3[1]);
    S.o[2] += o1[2] + (o2[2] + o3[2]); S.o[3] += o1[3] + (o2[3] + o3[3]);
}

__device__ __forceinline__ void flush_ctx(Ctx& S, uint32_t part, bool first, int lane, const LaneC& L) {
    float l = S.l;
#pragma unroll
    for (int o = 16; o > 0; o >>= 1) l += __shfl_xor_sync(0xffffffffu, l, o);
    const uint32_t a = part + (16 * L.t + L.g) * 4;
    float m = S.m;
    if (!first) {
        const float mo = ldsf(part + 512), lo = ldsf(part + 516);
        m = fmaxf(mo, S.m);
        const float fo = ex2(mo - m), fn = ex2(S.m - m);
        S.o[0] = S.o[0] * fn + ldsf(a) * fo; S.o[1] = S.o[1] * fn + ldsf(a + 32) * fo;
        S.o[2] = S.o[2] * fn + ldsf(a + 256) * fo; S.o[3] = S.o[3] * fn + ldsf(a + 288) * fo;
        l = l * fn + lo * fo;
        __syncwarp();
    }
    stsf(a, S.o[0]); stsf(a + 32, S.o[1]); stsf(a + 256, S.o[2]); stsf(a + 288, S.o[3]);
    if (lane == 0) { stsf(part + 512, m); stsf(part + 516, l); }
    S.o[0] = S.o[1] = S.o[2] = S.o[3] = 0.f; S.l = 0.f; S.m = -INFINITY;
    __syncwarp();
}

template <bool PF> __device__ __forceinline__ void tma2d(uint32_t dst, const CUtensorMap* map, int c0, int c1, uint32_t bar, uint64_t pol) {
    if (PF) asm volatile("cp.async.bulk.prefetch.tensor.2d.L2.global.tile [%0, {%1, %2}];" ::"l"(map), "r"(c0), "r"(c1) : "memory");
    else asm volatile("cp.async.bulk.tensor.2d.shared::cluster.global.tile.mbarrier::complete_tx::bytes.L2::cache_hint [%0], [%1, {%2, %3}], [%4], %5;"
                      ::"r"(dst), "l"(map), "r"(c0), "r"(c1), "r"(bar), "l"(pol) : "memory");
}
template <int ST, int I, bool PF> __device__ __forceinline__ void load_chunk(const Params& p, uint32_t dst, uint32_t bar, uint64_t pol) {
    const int cta = blockIdx.x;
    if (ST == 0) {
        tma2d<PF>(dst, &p.mwo, 128 * I, 32 * cta, bar, pol); tma2d<PF>(dst + 4096, &p.mwo, 128 * I + 64, 32 * cta, bar, pol);
    } else if (ST == 1 && I < 2) {
        tma2d<PF>(dst, &p.mw1, 16 * cta, 256 * I, bar, pol);
    } else if (ST == 1) {
#pragma unroll
        for (int i = 0; i < 4; i++) tma2d<PF>(dst + i * 2048, &p.mw2, 256 * (I - 2) + 64 * i, 16 * cta, bar, pol);
    } else {
        const int r = 128 * (cta & 3) + 32 * I, cc = 128 * (cta >> 2);
        tma2d<PF>(dst, &p.mwq, cc, r, bar, pol); tma2d<PF>(dst + 4096, &p.mwq, cc + 64, r, bar, pol);
    }
}
struct WBuf {
    uint32_t a[3], bar, par;
    __device__ __forceinline__ void wait3() { mbar_wait(bar, par); }
    __device__ __forceinline__ void wait4() { mbar_wait(bar + 8, par); }
    __device__ __forceinline__ void rotate() { const uint32_t x = a[0]; a[0] = a[1]; a[1] = a[2]; a[2] = x; par ^= 1; }
};
template <int ST, bool PF4> __device__ __forceinline__ void load_stage1(const Params& p, const WBuf& W, uint64_t pol) {
    if (ST == 1 && blockIdx.x >= NMLP) { mbar_arrive(W.bar); mbar_arrive(W.bar + 8); return; }
    mbar_expect_tx(W.bar, 3 * 8192);
    load_chunk<ST, 0, false>(p, W.a[0], W.bar, pol);
    load_chunk<ST, 1, false>(p, W.a[1], W.bar, pol);
    load_chunk<ST, 2, false>(p, W.a[2], W.bar, pol);
    if (PF4) load_chunk<ST, 3, true>(p, 0, 0, pol);
}
template <int ST, bool PF4> __device__ __forceinline__ void load_stage(const Params& p, const WBuf& W, uint64_t pol) {
    __syncwarp();
    if (elect_one()) load_stage1<ST, PF4>(p, W, pol);
    __syncwarp();
}
template <int ST> __device__ __forceinline__ void load_fourth(const Params& p, const WBuf& W, uint64_t pol) {
    __syncwarp();
    if (elect_one()) { mbar_expect_tx(W.bar + 8, 8192); load_chunk<ST, 3, false>(p, W.a[0], W.bar + 8, pol); }
    __syncwarp();
}
__device__ __forceinline__ void frag8(uint32_t (&f)[8][4], uint32_t a) {
#pragma unroll
    for (int u = 0; u < 4; u++) { ldsm4t(f[u], a ^ (u << 5)); ldsm4t(f[4 + u], (a ^ (u << 5)) + 2048); }
}
template <int N, int STRIDE, int HALF> __device__ __forceinline__ void ll_gather(const uint32_t* src, int n, uint32_t tag, uint32_t (&w)[N][4]) {
#pragma unroll
    for (int i = 0; i < N; i++) w[i][0] = w[i][1] = w[i][2] = w[i][3] = i < n ? 0u : tag;
    uint32_t it = 0;
    while (true) {
#pragma unroll
        for (int i = 0; i < N; i++) ld_w4(src + (HALF ? (i & 3) * STRIDE + (i >> 2) * HALF : i * STRIDE), miss4(w[i], tag), w[i]);
        bool miss = false;
#pragma unroll
        for (int i = 0; i < N; i++) miss |= miss4(w[i], tag);
        if (!__any_sync(0xffffffffu, miss)) break;
        SPIN_GUARD(it);
    }
}
__device__ __forceinline__ void pick4(float (&o)[4], const float (&a0)[4], const float (&a1)[4], const float (&a2)[4], const float (&a3)[4], int t) {
#pragma unroll
    for (int i = 0; i < 4; i++) o[i] = (t & 2) ? ((t & 1) ? a3[i] : a2[i]) : ((t & 1) ? a1[i] : a0[i]);
}
__device__ __forceinline__ void issue_fill(uint32_t fill, uint32_t dst, uint32_t bars, const Params& p, uint64_t pol) {
    const uint32_t fbar = bars + ((fill >> 4) & 0x7ff);
    const size_t foff = ((size_t)blockIdx.x << 19) + ((fill >> 16) << 13);
    const char* kbase = reinterpret_cast<const char*>(p.k);
    const char* vbase = reinterpret_cast<const char*>(p.v);
    mbar_expect_tx(fbar, SLOT_B);
    bulk_g2s(dst, kbase + foff, HALF_B, fbar, pol);
    bulk_g2s(dst + HALF_B, vbase + foff, HALF_B, fbar, pol);
    if (fill & 2) { bulk_prefetch(kbase + foff, HALF_B); bulk_prefetch(vbase + foff, HALF_B); }
}
__device__ __forceinline__ uint2 lds64u(uint32_t a) {
    uint2 r;
    asm volatile("ld.shared.v2.u32 {%0,%1}, [%2];" : "=r"(r.x), "=r"(r.y) : "r"(a) : "memory");
    r.x = __shfl_sync(0xffffffffu, r.x, 0); r.y = __shfl_sync(0xffffffffu, r.y, 0);
    return r;
}

__device__ __forceinline__ float gelu_tanh(float x) {
    const float u = 0.7978845608028654f * (x + 0.044715f * x * x * x);
    const float th = 1.f - 2.f / (__expf(2.f * u) + 1.f);
    return 0.5f * x * (1.f + th);
}

template <int NB> __device__ __forceinline__ void gather_o(const uint32_t* src, int lane_off, uint32_t tag, bool live, float (&o)[NB]) {
    uint32_t wm[4 * NB], wl[4 * NB], wo[4 * NB];
#pragma unroll
    for (int i = 0; i < 4 * NB; i++) wm[i] = wl[i] = wo[i] = live ? 0u : tag;
    uint32_t it = 0;
    while (true) {
#pragma unroll
        for (int i = 0; i < 4 * NB; i++) {
            const uint32_t* q = src + (i >> 2) * (NCTA * 160) + (i & 3) * 160;
            ld_w2(q + 128, (((wm[i] ^ tag) | (wl[i] ^ tag)) & 15u) != 0, wm[i], wl[i]);
            ld_w1(q + lane_off, ((wo[i] ^ tag) & 15u) != 0, wo[i]);
        }
        uint32_t miss = 0;
#pragma unroll
        for (int i = 0; i < 4 * NB; i++) miss |= (wm[i] ^ tag) | (wl[i] ^ tag) | (wo[i] ^ tag);
        if (!__any_sync(0xffffffffu, (miss & 15u) != 0)) break;
        SPIN_GUARD(it);
    }
#pragma unroll
    for (int b = 0; b < NB; b++) {
        const float M = fmaxf(fmaxf(ll_val(wm[4 * b]), ll_val(wm[4 * b + 1])), fmaxf(ll_val(wm[4 * b + 2]), ll_val(wm[4 * b + 3])));
        float Ls = 0.f, O = 0.f;
#pragma unroll
        for (int i = 4 * b; i < 4 * b + 4; i++) { const float f = ex2(ll_val(wm[i]) - M); Ls += ll_val(wl[i]) * f; O += ll_val(wo[i]) * f; }
        o[b] = O / Ls;
    }
}
__device__ __forceinline__ void bar256() { asm volatile("bar.sync 1, 256;" ::: "memory"); }
__device__ __forceinline__ void red_sf(uint32_t a, float v) { asm volatile("red.shared.add.f32 [%0], %1;" ::"r"(a), "f"(v) : "memory"); }
__device__ __forceinline__ void fill_ones(uint32_t a, int lane) {
    const uint32_t o[4] = {0x3f803f80u, 0x3f803f80u, 0x3f803f80u, 0x3f803f80u};
    sts128(a + lane * 16, o); sts128(a + 512 + lane * 16, o);
}
__device__ __forceinline__ void ln_store2(const float (&x)[2][16], uint32_t xn, int lane) {
    float s[2] = {0.f, 0.f}, q[2] = {0.f, 0.f};
#pragma unroll
    for (int i = 0; i < 32; i++) s[i >> 4] += x[i >> 4][i & 15];
#pragma unroll
    for (int o = 16; o > 0; o >>= 1) { s[0] += __shfl_xor_sync(0xffffffffu, s[0], o); s[1] += __shfl_xor_sync(0xffffffffu, s[1], o); }
    s[0] *= (1.f / DM); s[1] *= (1.f / DM);
#pragma unroll
    for (int i = 0; i < 32; i++) { const float d = x[i >> 4][i & 15] - s[i >> 4]; q[i >> 4] += d * d; }
#pragma unroll
    for (int o = 16; o > 0; o >>= 1) { q[0] += __shfl_xor_sync(0xffffffffu, q[0], o); q[1] += __shfl_xor_sync(0xffffffffu, q[1], o); }
#pragma unroll
    for (int b = 0; b < 2; b++) {
        const float r = rsqrtf(q[b] * (1.f / DM) + 1e-5f), mean = s[b];
#pragma unroll
        for (int i = 0; i < 4; i++)
            sts64(xn + b * XS + (128 * i + 4 * lane) * 2, pack_bf16((x[b][4 * i] - mean) * r, (x[b][4 * i + 1] - mean) * r),
                  pack_bf16((x[b][4 * i + 2] - mean) * r, (x[b][4 * i + 3] - mean) * r));
    }
}

__global__ void __launch_bounds__(384, 1) fused_kernel(const __grid_constant__ Params p) {
    extern __shared__ __align__(1024) unsigned char smem_raw[];
    const uint32_t sb = (uint32_t)__cvta_generic_to_shared(smem_raw);
    const int tid = threadIdx.x, lane = tid & 31;
    const int warp = __shfl_sync(0xffffffffu, tid >> 5, 0);
    const int cta = blockIdx.x;

    const uint32_t bars = sb + SM_BAR;
    if (tid == 0) TSYNC(0);
    uint64_t pol;
    asm volatile("createpolicy.fractional.L2::evict_first.b64 %0, 1.0;" : "=l"(pol));
    WBuf W;
    W.a[0] = sb + SM_W; W.a[1] = sb + SM_W + 8192; W.a[2] = sb + SM_W + 16384; W.bar = bars + BAR_W * 8; W.par = 0;
    if (warp == 0) {
        if (elect_one()) {
#pragma unroll
            for (int k = 0; k < 3; k++) mbar_init(bars + (BAR_FULL + k) * 8, 1);
            mbar_init(bars + BAR_TAB * 8, 1);
            asm volatile("fence.mbarrier_init.release.cluster;" ::: "memory");
            mbar_expect_tx(bars + BAR_TAB * 8, TAB_BYTES);
            asm volatile("cp.async.bulk.shared::cluster.global.mbarrier::complete_tx::bytes [%0], [%1], %2, [%3];"
                         ::"r"(sb + SM_TAB), "l"(&g_tab), "r"(TAB_BYTES), "r"(bars + BAR_TAB * 8) : "memory");
            issue_fill(INITA0, sb, bars, p, pol);
            issue_fill(INITA1, sb + SLOT_B, bars, p, pol);
            issue_fill(INITA2, sb + 2 * SLOT_B, bars, p, pol);
        }
    } else if (warp == 3) {
#pragma unroll
        for (int i = 0; i < 4; i++) cp16(sb + SM_XN + (i >> 1) * XS + (i & 1) * 512 + lane * 16, p.x + 256 * i + 8 * lane);
        if (lane < 2) cp16(sb + SM_BIAS + lane * 16, p.b2 + 16 * (cta & 31) + 8 * lane);
        else if (lane < 4 && cta < NMLP) cp16(sb + SM_BIAS + lane * 16, p.b1 + 16 * cta + 8 * (lane - 2));
        else if (lane == 4) asm volatile("cp.async.ca.shared.global [%0], [%1], 4;" ::"r"(sb + SM_EPOCH), "l"(&g_epoch) : "memory");
        if (elect_one()) {
            asm volatile("prefetch.tensormap [%0];" ::"l"(&p.mwq) : "memory");
            mbar_init(W.bar, 1); mbar_init(W.bar + 8, 1);
            asm volatile("fence.mbarrier_init.release.cluster;" ::: "memory");
            load_stage1<2, true>(p, W, pol);
        }
    } else if (warp >= 4) {
        if (elect_one()) {
            for (int i = warp - 1; i < NBAR; i += 8) {
                if (i == BAR_TAB || i == BAR_W || i == BAR_W + 1) continue;
                int cnt = 1;
                if ((i >= BAR_CAP && i < BAR_FREE) || (i >= BAR_DUMP && i < BAR_Q)) cnt = 8;
                if (i >= BAR_CTX && i < BAR_TAB) cnt = 6;
                mbar_init(bars + i * 8, cnt);
            }
            asm volatile("fence.mbarrier_init.release.cluster;" ::: "memory");
        }
    }
    static_assert(NBAR <= 256, "set-up mapping");
    __syncthreads();

    if (warp >= 4) {
        asm volatile("setmaxnreg.inc.sync.aligned.u32 %0;" ::"n"(P_REG_HI));
        const uint32_t mine = sb + (tid - 128) * 16 + ((tid >> 5) - 4) * (2048 - 512);
        uint32_t r[NRF][16];
#pragma unroll
        for (int u = 0; u < NRF; u++)
#pragma unroll
            for (int c = 0; c < 16; c++) r[u][c] = 0;
        int nc = 0, nd = 0, uc = 0, ud = 0;
        unsigned long long cs = CAP0, ds = DUMP0;
        uint32_t it = 0;
        while (nd < 2 * NRF) {
            const bool canD = nd < nc, canC = nc < 2 * NRF && nc < nd + NRF;
            const uint32_t bd = bars + (BAR_FREE + nd) * 8, bc = bars + (BAR_RF + nc) * 8;
            if (!canC) mbar_wait_long(bd);
            if (!canD) mbar_wait_long(bc);
            if (canC && mbar_test_warp(bc, 0)) {
                const uint32_t a = mine + (uint32_t)(cs & 15) * SLOT_B;
                raw_dispatch<0, NRF, true>(r, uc, a);
                __syncwarp();
                if (lane == 0) mbar_arrive(bc + (BAR_CAP - BAR_RF) * 8);
                nc++; cs >>= 4;
                if (++uc == NRF) { uc = 0; cs = CAP1; }
                it = 0;
            } else if (canD && mbar_test_warp(bd, 0)) {
                const uint32_t a = mine + (uint32_t)(ds & 15) * SLOT_B;
                raw_dispatch<0, NRF, false>(r, ud, a);
                __syncwarp();
                if (lane == 0) mbar_arrive(bd + (BAR_DUMP - BAR_FREE) * 8);
                nd++; ds >>= 4;
                if (++ud == NRF) { ud = 0; ds = DUMP1; }
                it = 0;
            } else {
                __nanosleep(200);
                if (++it > (1u << 24)) __trap();
            }
        }
        {
            const int sw = __shfl_sync(0xffffffffu, (threadIdx.x >> 5) - 4, 0), g = lane >> 2, t = lane & 3;
            const int vrow = (lane & 7) + 8 * (lane >> 4);
            const uint32_t aoff = vrow * 128 + ((((lane >> 3) & 1) ^ (lane & 7)) << 4);
            const uint32_t wb = sb + SM_W, wbar = bars + BAR_W * 8;
            const bool mlp = cta < NMLP, owner = cta >= 64;
            const int ob = cta >= 96 ? 0 : 1, oo = cta & 31;
            uint32_t fo[8][4], f1[4][4], f2[4][4];
            mbar_wait(wbar, 1);
            if (sw < 6) frag8(fo, wb + (((sw >> 1) + 1) % 3) * 8192 + aoff + (sw & 1) * 4096);
            bar256();
            if (tid == 128) { mbar_expect_tx(wbar, 8192); load_chunk<0, 3, false>(p, wb, wbar, pol); }
            mbar_wait(wbar, 0);
            if (sw >= 6) frag8(fo, wb + aoff + (sw & 1) * 4096);
            bar256();
            const uint32_t my = wb + sw * 1024, redH = wb + 8192, redO = wb + 8192 + 512;
            if (lane < 4) sts32(my + 160 + lane * 4, 0x3f803f80u);
            const uint32_t vb = my + (lane & 1) * 80 + (lane >> 3) * 16;
            const uint32_t xb = (lane & 2) ? my + 160 : my + 256 + (lane & 1) * 144 + (lane >> 3) * 16;
            const uint32_t xs = (lane & 2) ? 0 : 64;
            const uint32_t epoch = lds32(sb + SM_EPOCH);
            const uint32_t tag0 = epoch % 15u + 1u, tagA = ((epoch % 15u) * 6u + 6u) % 15u + 1u, tagB = ((epoch % 15u) * 6u + 7u) % 15u + 1u;
            const float bias = mlp ? bf_lo(lds16(sb + SM_BIAS + 32 + (g + 4 * (t & 2)) * 2)) : 0.f;
            uint32_t* const outbox = &g_inbox[0][4 * sw + t][cta][g];
            constexpr int OB = 32 * NCTA * 16;
            mbar_wait_long(bars + (BAR_PRE + 3) * 8);
#pragma unroll 1
            for (int pass = 0; pass < 2; pass++) {
                const bool live = pass;
                const uint32_t keep = live ? 0xffffffffu : 0u;
                auto send4 = [&](const float (&acc)[4][4], uint32_t tag) {
                    float o[4];
                    pick4(o, acc[0], acc[1], acc[2], acc[3], t);
                    st_w(outbox, ll_pack(o[0], tag) & keep); st_w(outbox + 8, ll_pack(o[2], tag) & keep);
                    st_w(outbox + OB, ll_pack(o[1], tag) & keep); st_w(outbox + OB + 8, ll_pack(o[3], tag) & keep);
                };
                auto own = [&](int st, uint32_t tag) {
                    uint32_t w[2][4];
                    ll_gather<2, 128, 0>(&g_inbox[ob][oo][0][0] + sw * 256 + 4 * lane, (live && !(st && sw == 7)) ? 2 : 0, tag, w);
                    float c[4];
#pragma unroll
                    for (int e = 0; e < 4; e++) {
                        c[e] = ll_val(w[0][e]) + ll_val(w[1][e]);
                        c[e] += __shfl_xor_sync(0xffffffffu, c[e], 4); c[e] += __shfl_xor_sync(0xffffffffu, c[e], 8); c[e] += __shfl_xor_sync(0xffffffffu, c[e], 16);
                    }
                    if (lane < 4) sts128(redO + st * 512 + sw * 64 + lane * 16, reinterpret_cast<const uint32_t*>(c));
                    bar256();
                    if (sw == 0) {
                        uint32_t u[4], v[4];
                        lds128(u, redO + st * 512 + (lane >> 2) * 64 + t * 16);
                        lds128(v, sb + SM_XO + t * 16);
                        const uint32_t b01 = lds32(sb + SM_BIAS + t * 8), b23 = lds32(sb + SM_BIAS + t * 8 + 4);
                        float x[4];
#pragma unroll
                        for (int e = 0; e < 4; e++) {
                            float y = __uint_as_float(u[e]);
                            y += __shfl_xor_sync(0xffffffffu, y, 4); y += __shfl_xor_sync(0xffffffffu, y, 8); y += __shfl_xor_sync(0xffffffffu, y, 16);
                            const float b2 = e == 0 ? bf_lo(b01) : (e == 1 ? bf_hi(b01) : (e == 2 ? bf_lo(b23) : bf_hi(b23)));
                            x[e] = bfr(__uint_as_float(v[e]) + (st == 0 ? bfr(y) : bfr(bfr(y) + b2)));
                        }
                        if (st == 0) {
                            if (lane < 4 * XR) st_w4(&g_xrow[2 + ob][(lane >> 2) % XR][16 * oo + 4 * t], (__float_as_uint(x[0]) | tag) & keep, (__float_as_uint(x[1]) | tag) & keep,
                                                     (__float_as_uint(x[2]) | tag) & keep, (__float_as_uint(x[3]) | tag) & keep);
                            __syncwarp();
                            if (live && lane < 4) sts128(sb + SM_XO + t * 16, reinterpret_cast<const uint32_t*>(x));
                            __syncwarp();
                        } else if (live && lane < 4) {
                            *reinterpret_cast<uint2*>(p.out + ob * DM + 16 * oo + 4 * lane) = make_uint2(pack_bf16(x[0], x[1]), pack_bf16(x[2], x[3]));
                        }
                    }
                };
                if (sw == 0) { sts32(redH + lane * 4, 0); sts32(redH + 128 + lane * 4, 0); }
                float o[2];
                if (live) {
                    mbar_wait_long(bars + (BAR_CTX + 3) * 8);
                    if (tid == 128 && mlp) {
                        mbar_expect_tx(wbar, 4 * 8192);
                        load_chunk<1, 0, false>(p, sb, wbar, pol); load_chunk<1, 1, false>(p, sb + 8192, wbar, pol);
                        load_chunk<1, 2, false>(p, sb + 16384, wbar, pol); load_chunk<1, 3, false>(p, sb + 24576, wbar, pol);
                    }
                }
                gather_o<2>(g_opart[2][cta & ~3], 32 * (cta & 3) + lane, tag0, live, o);
                if (live && sw == 0) TS(32 + 48 + 1);
                sts16(my + lane * 2, pack_bf16(o[0], 0.f)); sts16(my + 80 + lane * 2, pack_bf16(o[1], 0.f));
                __syncwarp();
                uint32_t bx[4];
                ldsm4(bx, vb);
                float acc[4][4];
#pragma unroll
                for (int u = 0; u < 4; u++) { acc[u][0] = acc[u][1] = acc[u][2] = acc[u][3] = 0.f; mma16816(acc[u], fo[u], bx[0], bx[1]); }
#pragma unroll
                for (int u = 0; u < 4; u++) mma16816(acc[u], fo[4 + u], bx[2], bx[3]);
                send4(acc, tagA);
                if (live && sw == 0) TS(32 + 48 + 2);
                if (owner) own(0, tagA); else bar256();
                if (live && sw == 0) TS(32 + 48 + 3);
                if (mlp) {
                    if (live) mbar_wait(wbar, 1);
#pragma unroll
                    for (int u = 0; u < 4; u++) {
                        ldsm4t(f1[u], sb + sw * 2048 + vrow * 32 + ((((lane >> 3) ^ (lane >> 2)) & 1) << 4) + u * 512);
                        ldsm4t(f2[u], ((sb + 16384 + sw * 2048 + aoff) ^ (u << 5)));
                    }
                    uint32_t w[1][4];
                    ll_gather<1, 0, 0>(g_xrow[2 + (lane >> 4)][cta % XR] + 64 * sw + 4 * (lane & 15), live, tagA, w);
                    if (live && sw == 0) TS(32 + 48 + 8);
                    sts64(my + 256 + (lane >> 4) * 144 + (lane & 15) * 8, __byte_perm(w[0][0], w[0][1], 0x7632), __byte_perm(w[0][2], w[0][3], 0x7632));
                    __syncwarp();
                    uint32_t b0[4], b1[4];
                    ldsm4(b0, xb); ldsm4(b1, xb + xs);
#pragma unroll
                    for (int u = 0; u < 4; u++) acc[u][0] = acc[u][1] = acc[u][2] = acc[u][3] = 0.f;
                    mma16816(acc[0], f1[0], b0[0], b0[1]); mma16816(acc[1], f1[1], b0[2], b0[3]);
                    mma16816(acc[2], f1[2], b1[0], b1[1]); mma16816(acc[3], f1[3], b1[2], b1[3]);
                    const float x0 = ll_val(w[0][0]), x1 = ll_val(w[0][1]), x2 = ll_val(w[0][2]), x3 = ll_val(w[0][3]);
                    float s1 = (x0 + x1) + (x2 + x3), s2 = (x0 * x0 + x1 * x1) + (x2 * x2 + x3 * x3);
#pragma unroll
                    for (int q = 8; q > 0; q >>= 1) { s1 += __shfl_xor_sync(0xffffffffu, s1, q); s2 += __shfl_xor_sync(0xffffffffu, s2, q); }
                    if (!(lane & 15)) { red_sf(redH + 192 + (lane >> 4) * 8, s1); red_sf(redH + 196 + (lane >> 4) * 8, s2); }
                    float h4[4];
#pragma unroll
                    for (int i = 0; i < 4; i++) h4[i] = (acc[0][i] + acc[1][i]) + (acc[2][i] + acc[3][i]);
                    const float ha = (t & 2) ? h4[2] : h4[0], hb = (t & 2) ? h4[3] : h4[1];
                    const int unit = g + 4 * (t & 2);
                    if (t & 1) red_sf(redH + 128 + unit * 4, ha);
                    else { red_sf(redH + unit * 8, ha); red_sf(redH + unit * 8 + 4, hb); }
                    bar256();
                    const float hv = ldsf(redH + unit * 8 + (t & 1) * 4), sw1 = ldsf(redH + 128 + unit * 4);
                    const float mean = ldsf(redH + 192 + (t & 1) * 8) * (1.f / DM);
                    const float rs = rsqrtf(fmaxf(ldsf(redH + 196 + (t & 1) * 8) * (1.f / DM) - mean * mean, 0.f) + 1e-5f);
                    sts16(my + (t & 1) * 80 + unit * 2, pack_bf16(gelu_tanh(bfr(bfr((hv - mean * sw1) * rs) + bias)), 0.f));
                    __syncwarp();
                    ldsm4(bx, vb);
#pragma unroll
                    for (int u = 0; u < 4; u++) { acc[u][0] = acc[u][1] = acc[u][2] = acc[u][3] = 0.f; mma16816(acc[u], f2[u], bx[0], bx[1]); }
                    if (live) send4(acc, tagB);
                    if (live && sw == 0) TS(32 + 48 + 5);
                }
                if (owner) own(1, tagB); else bar256();
                if (live && sw == 0) TS(32 + 48 + 6);
            }
            if (tid == 128) TSYNC(1);
            if (cta == NCTA - 1 && tid == 128) asm volatile("st.relaxed.gpu.global.u32 [%0], %1;" ::"l"(&g_epoch), "r"(epoch + 1) : "memory");
        }
    } else {
        asm volatile("setmaxnreg.dec.sync.aligned.u32 %0;" ::"n"(P_REG_LO));
        LaneC L;
        L.g = lane >> 2; L.t = lane & 3; L.v = (L.g >> 1) ^ L.t;
        L.src0 = 9 * L.t + 4 * (L.g & 1); L.src1 = 9 * L.t + 4 * ((L.g & 1) ^ 1);
        L.sx0 = (L.g & 1) ? 0x1044u : 0x4410u; L.sy0 = (L.g & 1) ? 0x3244u : 0x4432u;
        L.vrow = (lane & 7) + 8 * (lane >> 4);
        L.voff = ((lane >> 3) & 1) * 128 + ((lane & 7) << 4);

        if (warp < 3) {
            const int w = __shfl_sync(0xffffffffu, threadIdx.x >> 5, 0);
            const uint32_t koff = ((lane & 7) + 8 * ((lane >> 3) & 1)) * 256 + (((lane >> 4) ^ (lane & 7)) << 4);
            const uint32_t voff = HALF_B + L.vrow * 256 + L.voff;
            const int qrow = 4 * (L.g & 3) + L.t;
            const uint32_t qoff = sb + SM_Q + qrow * 64 + (((L.g >> 2) ^ ((qrow >> 1) & 3)) << 4);
            Ctx SA, SB;
            SA.o[0] = SA.o[1] = SA.o[2] = SA.o[3] = 0.f; SA.l = 0.f; SA.m = -INFINITY;
            SB = SA;
            uint32_t pa = sb + SM_TAB + w * LA * 8, pb = sb + SM_TAB + (3 * LA + w * LB) * 8;
            mbar_wait(bars + BAR_TAB * 8, 0);
            uint2 dA = lds64u(pa), dB = lds64u(pb);
            uint32_t flushed = 0, idle = 0;
            auto run = [&](const uint2 d, Ctx& S, int ring) {
                const uint32_t tile = sb + ((d.x >> 16) & 15) * SLOT_B;
                const int ctx = (d.x >> 14) & 3;
                if (!(d.x & D_NOPROC)) process_tile(S, tile, qoff + (ctx & 1) * 1024, koff, voff, L, d.y, bars, p, pol);
                else if (((d.y & 7) - 1u) < 2u) {
                    if (elect_one()) issue_fill(d.y, tile, bars, p, pol);
                    __syncwarp();
                }
                if ((d.y & 7) == F_FREE) { __syncwarp(); if (lane == 0) mbar_arrive(bars + ((d.y >> 4) & 0x7ff)); }
                if (d.x & (D_FLUSH | D_PRE)) {
                    if (d.x & D_FLUSH) {
                        flush_ctx(S, sb + SM_PART + ((ctx & 1) * 3 + w) * 528, !((flushed >> ctx) & 1), lane, L);
                        flushed |= 1u << ctx;
                        TS(ring * 12 + ctx * 3 + w);
                    }
                    if (lane == 0) mbar_arrive(bars + (((d.x & D_FLUSH) ? BAR_CTX : BAR_PRE) + ctx) * 8);
                }
            };
            while (true) {
                if (!(dA.x & D_END) && mbar_test_warp(bars + (dA.x & 0x7ff), (dA.x >> 11) & 1)) {
                    const uint2 d = dA;
                    pa += 8; dA = lds64u(pa);
                    run(d, SA, 0);
                    TS(128 + w * LB + ((pa - 8 - sb - SM_TAB) >> 3));
                } else if (!(dB.x & D_END) && mbar_test_warp(bars + (dB.x & 0x7ff), (dB.x >> 11) & 1)) {
                    const uint2 d = dB;
                    pb += 8; dB = lds64u(pb);
                    run(d, SB, 1);
                    TS(128 + w * (LA + LB) + LA + ((pb - 8 - sb - SM_TAB - (3 * LA + w * LB) * 8) >> 3));
                } else {
                    if (dA.x & dB.x & D_END) break;
                    if (++idle > (1u << 25)) __trap();
                    continue;
                }
                idle = 0;
            }
        } else {
            TS(24);
            const int ob = cta >= 96 ? 0 : 1, oo = cta & 31;
            asm volatile("cp.async.wait_all;" ::: "memory");
            __syncwarp();
            const uint32_t epoch = lds32(sb + SM_EPOCH);
            if (lane < 16) stsf(sb + SM_XO + lane * 4, bf_lo(lds16(sb + SM_XN + ob * XS + (16 * oo + lane) * 2)));
            __syncwarp();
            const uint32_t tag0 = epoch % 15u + 1u, ubase = (epoch % 15u) * 6u;
            const uint32_t xnb = sb + SM_XN;
            const uint32_t aoff = L.vrow * 128 + ((((lane >> 3) & 1) ^ (lane & 7)) << 4);
            const uint32_t vb = sb + SM_V + (lane >> 3) * 16;
            const uint32_t xb = xnb + (lane & 1) * XS + (lane >> 3) * 16;
            auto reset_o = [&](int ctx) {
                int l = lane; asm volatile("" : "+r"(l));
                uint32_t* dst = g_opart[ctx][cta] + l;
#pragma unroll
                for (int i = 0; i < 4; i++) st_w(dst + 32 * i, 0);
                if (lane < 8) st_w(dst + 128, 0);
            };
            auto publish = [&](int ctx) {
                mbar_wait(bars + (BAR_CTX + ctx) * 8, 0);
                const uint32_t pa = sb + SM_PART + (ctx & 1) * 3 * 528;
                const float m0 = ldsf(pa + 512), m1 = ldsf(pa + 528 + 512), m2 = ldsf(pa + 1056 + 512);
                const float Mt = ll_val(__float_as_uint(fmaxf(m0, fmaxf(m1, m2))));
                const float f0 = ex2(m0 - Mt), f1 = ex2(m1 - Mt), f2 = ex2(m2 - Mt);
                int l = lane; asm volatile("" : "+r"(l));
                uint32_t* dst = g_opart[ctx][cta] + l;
#pragma unroll
                for (int i = 0; i < 4; i++) {
                    const uint32_t a = pa + (l + 32 * i) * 4;
                    ll_store(dst + 32 * i, ldsf(a) * f0 + ldsf(a + 528) * f1 + ldsf(a + 1056) * f2, tag0);
                }
                if (lane < 8) ll_store(dst + 128, lane ? ldsf(pa + 516) * f0 + ldsf(pa + 528 + 516) * f1 + ldsf(pa + 1056 + 516) * f2 : Mt, tag0);
            };
#pragma unroll 1
            for (int gi = 0; gi < 5; gi++) {
                const int h = cta >> 2, j = cta & 3, bb = (gi - 1) & 1;
                const bool owner = cta >= 64 && ob == bb;
                auto fresh = [&]() { int l = lane; asm volatile("" : "+r"(l)); return l; };
                auto outbox_p = [&]() { const int l = fresh(); return &g_inbox[bb][l & 3][cta][l >> 2]; };
                auto qout_p = [&]() { const int l = fresh(); return g_qpart[gi ? 2 + bb : 0][cta] + 16 * (l & 3) + (l >> 2); };
                auto xout_p = [&]() { const int l = fresh(); return &g_xrow[ob][(l >> 2) % XR][16 * oo + 4 * (l & 3)]; };
                if (gi != 3) {
                    if (gi) { mbar_wait_long(bars + (BAR_PRE + gi - 1) * 8); reset_o(gi - 1); }
                    if (gi < 3) {
                        uint32_t* const qout = qout_p();
                        uint32_t* const outbox = outbox_p();
                        st_w(qout, 0); st_w(qout + 8, 0); st_w(qout + 64, 0); st_w(qout + 72, 0);
                        if (gi) {
#pragma unroll
                            for (int i = 0; i < 8; i++) { st_w(outbox + i * 4 * NCTA * 16, 0); st_w(outbox + i * 4 * NCTA * 16 + 8, 0); }
                            if (owner && lane < 4 * XR) st_w4(xout_p(), 0, 0, 0, 0);
                        } else {
                            st_w(qout + NCTA * 128, 0); st_w(qout + NCTA * 128 + 8, 0); st_w(qout + NCTA * 128 + 64, 0); st_w(qout + NCTA * 128 + 72, 0);
                        }
                    }
                }
                if (gi >= 3) { publish(gi - 1); TS(32 + 48); continue; }
#pragma unroll 1
                for (int st = (gi == 0 ? 2 : 0); st < 3; st++) {
                    const uint32_t tag = (ubase + 2 * gi + st) % 15u + 1u, tagp = (ubase + 2 * gi + st + 14u) % 15u + 1u;
                    uint32_t f[2][8][4];
                    if (gi == 0) {
                        float x[2][16];
#pragma unroll
                        for (int i = 0; i < 8; i++) {
                            uint32_t v[2];
                            asm volatile("ld.shared.v2.u32 {%0,%1}, [%2];" : "=r"(v[0]), "=r"(v[1]) : "r"(xnb + (i >> 2) * XS + (128 * (i & 3) + 4 * lane) * 2) : "memory");
                            float* xx = &x[i >> 2][4 * (i & 3)];
                            xx[0] = bf_lo(v[0]); xx[1] = bf_hi(v[0]); xx[2] = bf_lo(v[1]); xx[3] = bf_hi(v[1]);
                        }
                        ln_store2(x, xnb, lane);
                    }
                    W.wait3();
                    const uint32_t o1w = L.vrow * 32 + ((((lane >> 3) ^ (lane >> 2)) & 1) << 4);
#pragma unroll
                    for (int k = 0; k < 4; k++) {
                        const uint32_t a = W.a[0] + (st == 1 ? o1w + k * 512 : aoff ^ (k << 5));
#pragma unroll
                        for (int u = 0; u < 4; u++) ldsm4t(f[u >> 1][4 * (u & 1) + k], a + u * 2048);
                    }
                    if (st == 0) load_fourth<0>(p, W, pol);
                    else if (st == 2) load_fourth<2>(p, W, pol);
                    else if (cta < NMLP) load_fourth<1>(p, W, pol);
                    if (st == 0) {
                        publish(bb);
                        TS(32 + gi * 16);
                        float o1[1];
                        gather_o<1>(g_opart[bb][4 * h], 32 * j + fresh(), tag0, true, o1);
                        sts16(sb + SM_V + lane * 2, pack_bf16(o1[0], 0.f));
                        __syncwarp();
                        uint32_t bx[4];
                        ldsm4(bx, vb);
                        TS(32 + gi * 16 + 1);
                        {
                            uint32_t* const outbox = outbox_p();
                            uint32_t* d = outbox;
#pragma unroll 1
                            for (int c = 0; c < 4; c++) {
                                if (c == 2) W.wait4();
                                const uint32_t nx = (c == 0 ? W.a[1] : (c == 1 ? W.a[2] : W.a[0])) + aoff;
#pragma unroll
                                for (int hf = 0; hf < 2; hf++) {
                                    float acc[4][4], o[4];
#pragma unroll
                                    for (int u = 0; u < 4; u++) {
                                        acc[u][0] = acc[u][1] = acc[u][2] = acc[u][3] = 0.f;
                                        mma16816(acc[u], f[hf][u], bx[0], bx[1]);
                                    }
#pragma unroll
                                    for (int u = 0; u < 4; u++) mma16816(acc[u], f[hf][4 + u], bx[2], bx[3]);
                                    frag8(f[hf], nx + hf * 4096);
                                    pick4(o, acc[0], acc[1], acc[2], acc[3], L.t);
                                    ll_store(d, o[0], tag); ll_store(d + 8, o[2], tag);
                                    d += 4 * NCTA * 16;
                                }
                            }
                        }
                        W.rotate();
                        TS(32 + gi * 16 + 2);
                        if (!owner) load_stage<1, false>(p, W, pol);
                    } else {
                        float s1 = 0.f, s2 = 0.f;
                        if (gi && (st == 2 || cta < NMLP)) {
                            uint32_t w[4][4];
                            ll_gather<4, 128, 0>(g_xrow[bb][cta % XR] + 4 * fresh(), 4, tagp, w);
                            TS(32 + gi * 16 + 7 + st);
                            float u[4], v[4];
#pragma unroll
                            for (int i = 0; i < 4; i++) {
                                sts64(xnb + (128 * i + 4 * lane) * 2, __byte_perm(w[i][0], w[i][1], 0x7632), __byte_perm(w[i][2], w[i][3], 0x7632));
                                const float x0 = ll_val(w[i][0]), x1 = ll_val(w[i][1]), x2 = ll_val(w[i][2]), x3 = ll_val(w[i][3]);
                                u[i] = (x0 + x1) + (x2 + x3);
                                v[i] = (x0 * x0 + x1 * x1) + (x2 * x2 + x3 * x3);
                            }
                            s1 = (u[0] + u[1]) + (u[2] + u[3]); s2 = (v[0] + v[1]) + (v[2] + v[3]);
                        }
                        __syncwarp();
                        auto row_stats = [&]() {
#pragma unroll
                            for (int o = 16; o > 0; o >>= 1) { s1 += __shfl_xor_sync(0xffffffffu, s1, o); s2 += __shfl_xor_sync(0xffffffffu, s2, o); }
                            s1 *= (1.f / DM);
                            s2 = rsqrtf(fmaxf(s2 * (1.f / DM) - s1 * s1, 0.f) + 1e-5f);
                        };
                        if (st == 2) {
                            float acc[8][4];
#pragma unroll
                            for (int u = 0; u < 8; u++) acc[u][0] = acc[u][1] = acc[u][2] = acc[u][3] = 0.f;
                            TS(32 + gi * 16 + 10);
                            {
                                uint32_t bx[4];
                                ldsm4(bx, xb + (128 * j) * 2);
#pragma unroll 1
                                for (int c = 0; c < 4; c++) {
                                    if (c == 2) W.wait4();
                                    const uint32_t nx = (c == 0 ? W.a[1] : (c == 1 ? W.a[2] : W.a[0])) + aoff;
                                    uint32_t bn[4];
                                    ldsm4(bn, xb + (128 * j + 32 * ((c + 1) & 3)) * 2);
#pragma unroll
                                    for (int hf = 0; hf < 2; hf++) {
#pragma unroll
                                        for (int u = 0; u < 4; u++) mma16816(acc[4 * hf + u], f[hf][u], bx[0], bx[1]);
#pragma unroll
                                        for (int u = 0; u < 4; u++) mma16816(acc[4 * hf + u], f[hf][4 + u], bx[2], bx[3]);
                                        frag8(f[hf], nx + hf * 4096);
                                    }
                                    bx[0] = bn[0]; bx[1] = bn[1]; bx[2] = bn[2]; bx[3] = bn[3];
                                    if (c == 0) row_stats();
                                }
                            }
                            W.rotate();
                            uint32_t* const qout = qout_p();
#pragma unroll
                            for (int q = 0; q < 2; q++) {
                                float o[4];
                                pick4(o, acc[4 * q], acc[4 * q + 1], acc[4 * q + 2], acc[4 * q + 3], L.t);
                                uint32_t* d = qout + 64 * q;
                                if (gi) { o[0] = (o[0] - s1 * o[1]) * s2; o[2] = (o[2] - s1 * o[3]) * s2; }
                                ll_store(d, o[0], tag0); ll_store(d + 8, o[2], tag0);
                                if (!gi) { ll_store(d + NCTA * 128, o[1], tag0); ll_store(d + NCTA * 128 + 8, o[3], tag0); }
                            }
                            TS(32 + gi * 16 + 11);
                            break;
                        }
                        TS(32 + gi * 16 + 12);
                        if (cta < NMLP) {
                            float hh[4][4];
#pragma unroll
                            for (int u = 0; u < 4; u++) hh[u][0] = hh[u][1] = hh[u][2] = hh[u][3] = 0.f;
#pragma unroll 1
                            for (int c = 0; c < 2; c++) {
                                uint32_t na[4];
#pragma unroll
                                for (int k = 0; k < 4; k++) na[k] = c == 0 ? W.a[1] + o1w + k * 512 : W.a[2] + (aoff ^ (k << 5));
#pragma unroll
                                for (int s = 0; s < 4; s++) {
                                    uint32_t b0[4], b1[4];
                                    ldsm4(b0, xb + 512 * c + 128 * s); ldsm4(b1, xb + 512 * c + 128 * s + 64);
                                    mma16816(hh[0], f[s >> 1][4 * (s & 1)], b0[0], b0[1]); mma16816(hh[1], f[s >> 1][4 * (s & 1) + 1], b0[2], b0[3]);
                                    mma16816(hh[2], f[s >> 1][4 * (s & 1) + 2], b1[0], b1[1]); mma16816(hh[3], f[s >> 1][4 * (s & 1) + 3], b1[2], b1[3]);
#pragma unroll
                                    for (int k = 0; k < 4; k++) ldsm4t(f[s >> 1][4 * (s & 1) + k], na[k] + s * 2048);
                                }
                                if (c == 0) row_stats();
                            }
                            float hs4[4];
#pragma unroll
                            for (int i = 0; i < 4; i++) hs4[i] = (hh[0][i] + hh[1][i]) + (hh[2][i] + hh[3][i]);
                            const float hv = (((L.t & 2) ? hs4[2] : hs4[0]) - s1 * ((L.t & 2) ? hs4[3] : hs4[1])) * s2;
                            const float bias = bf_lo(lds16(sb + SM_BIAS + 32 + (L.g + 4 * (L.t & 2)) * 2));
                            uint32_t* const outbox = outbox_p();
                            sts16(sb + SM_V + (L.g + 4 * (L.t & 2)) * 2, pack_bf16(gelu_tanh(bfr(bfr(hv) + bias)), 0.f));
                            __syncwarp();
                            uint32_t bx[4];
                            ldsm4(bx, vb);
                            W.wait4();
                            uint32_t* d = outbox;
#pragma unroll 1
                            for (int c = 0; c < 2; c++) {
#pragma unroll
                                for (int s = 0; s < 4; s++) {
                                    float acc[4][4], o[4];
#pragma unroll
                                    for (int u = 0; u < 4; u++) {
                                        acc[u][0] = acc[u][1] = acc[u][2] = acc[u][3] = 0.f;
                                        mma16816(acc[u], f[s >> 1][4 * (s & 1) + u], bx[0], bx[1]);
                                    }
#pragma unroll
                                    for (int u = 0; u < 4; u++) ldsm4t(f[s >> 1][4 * (s & 1) + u], W.a[0] + (aoff ^ (u << 5)) + s * 2048);
                                    pick4(o, acc[0], acc[1], acc[2], acc[3], L.t);
                                    ll_store(d, o[0], tag); ll_store(d + 8, o[2], tag);
                                    d += 4 * NCTA * 16;
                                }
                            }
                        }
                        W.rotate();
                        TS(32 + gi * 16 + 5);
                        if (!owner) load_stage<2, false>(p, W, pol);
                    }
                    if (owner) {
                        uint32_t w[16][4];
                        ll_gather<16, 128, 0>(&g_inbox[ob][oo][0][0] + 4 * fresh(), st == 0 ? 16 : NMLP / 8, tag, w);
                        float xown[4];
                        lds128(reinterpret_cast<uint32_t*>(xown), sb + SM_XO + (lane & 3) * 16);
                        const uint32_t b01 = lds32(sb + SM_BIAS + (lane & 3) * 8), b23 = lds32(sb + SM_BIAS + (lane & 3) * 8 + 4);
                        const float b2own[4] = {bf_lo(b01), bf_hi(b01), bf_lo(b23), bf_hi(b23)};
#pragma unroll
                        for (int e = 0; e < 4; e++) {
                            float c[4];
#pragma unroll
                            for (int i = 0; i < 4; i++) c[i] = (ll_val(w[i][e]) + ll_val(w[4 + i][e])) + (ll_val(w[8 + i][e]) + ll_val(w[12 + i][e]));
                            float t = (c[0] + c[1]) + (c[2] + c[3]);
                            t += __shfl_xor_sync(0xffffffffu, t, 4); t += __shfl_xor_sync(0xffffffffu, t, 8); t += __shfl_xor_sync(0xffffffffu, t, 16);
                            xown[e] = bfr(xown[e] + (st == 0 ? bfr(t) : bfr(bfr(t) + b2own[e])));
                        }
                        if (lane < 4 * XR) st_w4(xout_p(), __float_as_uint(xown[0]) | tag, __float_as_uint(xown[1]) | tag, __float_as_uint(xown[2]) | tag, __float_as_uint(xown[3]) | tag);
                        __syncwarp();
                        if (lane < 4) sts128(sb + SM_XO + lane * 16, reinterpret_cast<const uint32_t*>(xown));
                        TS(32 + gi * 16 + 3 + 3 * st);
                        if (st == 0) load_stage<1, false>(p, W, pol); else load_stage<2, false>(p, W, pol);
                    }
                }
                {
                    uint32_t w[8][4];
                    ll_gather<8, 128, NCTA * 128>(g_qpart[gi ? 2 + bb : 0][4 * h] + 4 * fresh(), gi ? 4 : 8, tag0, w);
#pragma unroll
                    for (int bi = 0; bi < 2; bi++) {
                        if (bi == 0 || gi == 0) {
                            float q[4];
#pragma unroll
                            for (int e = 0; e < 4; e++) q[e] = (ll_val(w[4 * bi][e]) + ll_val(w[4 * bi + 1][e])) + (ll_val(w[4 * bi + 2][e]) + ll_val(w[4 * bi + 3][e]));
                            const uint32_t w0 = pack_bf16(q[0], q[1]), w1 = pack_bf16(q[2], q[3]);
                            const int ch = lane >> 1;
#pragma unroll
                            for (int kp = 0; kp < 4; kp++) {
                                const int jj = ch ^ kp;
#pragma unroll
                                for (int e = 0; e < 2; e++) {
                                    const int row = 4 * kp + 2 * (lane & 1) + e;
                                    sts32(sb + SM_Q + (gi ? bb : bi) * 1024 + row * 64 + (((jj >> 2) ^ ((row >> 1) & 3)) << 4) + (jj & 3) * 4, e ? w1 : w0);
                                }
                            }
                        }
                    }
                    __syncwarp();
                    if (lane < (gi ? 1 : 2)) mbar_arrive(bars + (BAR_Q + (gi ? 2 + bb : lane)) * 8);
                }
                TS(32 + gi * 16 + 7);
                load_stage<0, false>(p, W, pol);
                if (gi == 0) fill_ones(xnb + XS, lane);
            }
        }
    }
}

typedef CUresult (*EncodeFn)(CUtensorMap*, CUtensorMapDataType, cuuint32_t, void*, const cuuint64_t*, const cuuint64_t*, const cuuint32_t*,
                             const cuuint32_t*, CUtensorMapInterleave, CUtensorMapSwizzle, CUtensorMapL2promotion, CUtensorMapFloatOOBfill);
void encode2d(EncodeFn fn, CUtensorMap* m, void* base, uint64_t cols, uint64_t rows, uint32_t bcols, uint32_t brows, CUtensorMapSwizzle sw) {
    const cuuint64_t dim[2] = {cols, rows}, stride[1] = {cols * 2};
    const cuuint32_t box[2] = {bcols, brows}, es[2] = {1, 1};
    fn(m, CU_TENSOR_MAP_DATA_TYPE_BFLOAT16, 2, base, dim, stride, box, es, CU_TENSOR_MAP_INTERLEAVE_NONE, sw,
       CU_TENSOR_MAP_L2_PROMOTION_L2_128B, CU_TENSOR_MAP_FLOAT_OOB_FILL_NONE);
}

}

extern "C" void kernel_launch(void* const* d_in, const int* in_sizes, int n_in, void* d_out, int out_size) {
    (void)in_sizes; (void)n_in; (void)out_size;
    static EncodeFn enc = nullptr;
    if (!enc) {
        cudaFuncSetAttribute(fused_kernel, cudaFuncAttributeMaxDynamicSharedMemorySize, (int)SM_TOTAL);
        void* fn = nullptr;
        cudaDriverEntryPointQueryResult qr;
        cudaGetDriverEntryPoint("cuTensorMapEncodeTiled", &fn, cudaEnableDefault, &qr);
        enc = (EncodeFn)fn;
    }
    Params p;
    encode2d(enc, &p.mwq, d_in[3], HD, DM, 64, 32, CU_TENSOR_MAP_SWIZZLE_128B);
    encode2d(enc, &p.mwo, d_in[4], DM, HD, 64, 32, CU_TENSOR_MAP_SWIZZLE_128B);
    encode2d(enc, &p.mw1, d_in[6], FF, DM, 16, 256, CU_TENSOR_MAP_SWIZZLE_32B);
    encode2d(enc, &p.mw2, d_in[8], DM, FF, 64, 16, CU_TENSOR_MAP_SWIZZLE_128B);
    p.x = (const __nv_bfloat16*)d_in[0];
    p.k = (const __nv_bfloat16*)d_in[1];
    p.v = (const __nv_bfloat16*)d_in[2];
    p.b1 = (const __nv_bfloat16*)d_in[7];
    p.b2 = (const __nv_bfloat16*)d_in[9];
    p.out = (__nv_bfloat16*)d_out;
    fused_kernel<<<NCTA, 384, SM_TOTAL>>>(p);
}
```

```cpp
#include <cuda_runtime.h>
#include <cuda.h>
#include <cuda_bf16.h>
#include <stdint.h>

namespace {

constexpr int NCTA = 128;
constexpr int DM = 512, FF = 1792, HD = 4096;
constexpr int NMLP = 112;
constexpr uint32_t HALF_B = 8192;
constexpr uint32_t SLOT_B = 16384;
constexpr int NT = 64;

constexpr int REG_LO = 104, REG_HI = 200;
constexpr int PRE = 2;
constexpr int MIX = 2;
constexpr int NSB = 3;
constexpr int NB = 3 * NSB, NSLOT = 3 + NB;
constexpr int NRF = 12;
constexpr int NL2 = 19;
constexpr int NNR = NT - NB - NRF - NL2;
constexpr int TB = NT - NB;
constexpr int NZ = NRF + NL2;

constexpr int BAR_FULL = 0;
constexpr int BAR_RF = NSLOT, BAR_CAP = BAR_RF + 2 * NRF, BAR_FREE = BAR_CAP + 2 * NRF, BAR_DUMP = BAR_FREE + 2 * NRF;
constexpr int BAR_Q = BAR_DUMP + 2 * NRF, BAR_CTX = BAR_Q + 4, BAR_TAB = BAR_CTX + 4, BAR_W = BAR_TAB + 1, BAR_PRE = BAR_W + 2, NBAR = BAR_PRE + 4;

enum { F_NONE = 0, F_TILE = 1, F_KEEP = 2, F_FREE = 4, F_NORM = 8 };
constexpr uint32_t D_NOPROC = 1u << 12, D_FLUSH = 1u << 13, D_PRE = 1u << 21, D_END = 1u << 31;
struct Desc { uint32_t w0, w1; };
constexpr int LA = 66, LB = 42;
struct Tables {
    Desc a[3][LA];
    Desc b[3][LB];
    uint32_t inita[4];
    int capslot[2][NRF], dumpslot[2][NRF];
    bool ok;
};
enum { K_TILE = 0, K_CAP = 1, K_L2 = 2, K_DUMP = 4, K_RES = 5 };
struct Item { int kind, ctx, idx; };
constexpr uint32_t mk0(int bar, int par, int ctx, int slot) { return (uint32_t)(bar * 8) | ((uint32_t)par << 11) | ((uint32_t)ctx << 14) | ((uint32_t)slot << 16); }
constexpr uint32_t mkfill(const Item& x, int slot) {
    const int b = x.ctx & 1;
    if (x.kind == K_DUMP) return F_FREE | ((uint32_t)((BAR_FREE + b * NRF + x.idx - NNR) * 8) << 4);
    if (x.kind == K_RES) return F_NONE;
    const int bar = x.kind == K_CAP ? BAR_RF + b * NRF + x.idx - NNR : BAR_FULL + slot;
    const uint32_t norm = x.ctx == 0 && (x.idx < NNR || x.idx >= TB) ? F_NORM : 0;
    return (x.kind == K_L2 ? F_KEEP : F_TILE) | norm | ((uint32_t)(bar * 8) << 4) | ((uint32_t)(b * 8192 + x.idx) << 16);
}
constexpr Tables build_tables() {
    Tables T{};
    T.ok = true;
    Item A[256] = {};
    int n = 0;
    auto tiles = [&](int kind, int ctx, int lo, int hi) { for (int i = lo; i < hi; i++) A[n++] = Item{kind, ctx, i}; };
    for (int c = 0; c < 2; c++) { tiles(K_TILE, c, 0, NNR); tiles(K_CAP, c, NNR, NNR + NRF); tiles(K_L2, c, NNR + NRF, TB); }
    tiles(K_TILE, 2, 0, NNR);
    tiles(K_TILE, 3, 0, NNR);
    const int NA = n;
    for (int w = 0; w < 3; w++) {
        int m = 0, par = 0, cur = -1;
        T.inita[w] = mkfill(A[w], w);
        for (int i = w; i < NA; i += 3) {
            const Item x = A[i];
            const uint32_t fill = i + 3 < NA ? mkfill(A[i + 3], w) : (uint32_t)F_NONE;
            if (x.ctx != cur) T.a[w][m++] = Desc{mk0(BAR_Q + x.ctx, 0, 0, w) | D_NOPROC, F_NONE};
            cur = x.ctx;
            int left = 0;
            for (int k = i + 3; k < NA; k += 3) if (A[k].ctx == cur) left++;
            const uint32_t fl = (left == 0 ? D_FLUSH : 0u) | (cur != 2 && w == 0 && left == PRE ? D_PRE : 0u);
            const int b = x.ctx & 1;
            if (x.kind == K_CAP) {
                T.capslot[b][x.idx - NNR] = w;
                T.a[w][m++] = Desc{mk0(BAR_RF + b * NRF + x.idx - NNR, 0, x.ctx, w) | fl, F_NONE};
                T.a[w][m++] = Desc{mk0(BAR_CAP + b * NRF + x.idx - NNR, 0, 0, w) | D_NOPROC, fill};
            } else {
                T.a[w][m++] = Desc{mk0(BAR_FULL + w, par, x.ctx, w) | fl, fill};
                par ^= 1;
            }
        }
        T.a[w][m++] = Desc{D_END, F_NONE};
        if (m > LA) T.ok = false;
        const int s0 = 3 + NSB * w;
        Item B[64] = {};
        int nb = 0;
        for (int h = 0; h < 2; h++) {
            for (int k = 0; k < NSB; k++) B[nb++] = Item{K_TILE, h, TB + s0 - 3 + k};
            for (int k = 0; k < NSB; k++) B[nb++] = Item{K_RES, 2 + h, 0};
            int zd = w, zl = NRF + (w + 3 - NRF % 3) % 3;
            while (zd < NRF || zl < NZ) {
                if (zd < NRF) { B[nb++] = Item{K_DUMP, 2 + h, NNR + zd}; zd += 3; }
                for (int k = 0; (k < MIX || zd >= NRF) && zl < NZ; k++) { B[nb++] = Item{K_TILE, 2 + h, NNR + zl}; zl += 3; }
            }
        }
        m = 0;
        int parb[NSB] = {};
        for (int k = 0; k < NSB; k++) T.b[w][m++] = Desc{mk0(BAR_FULL + (k ? s0 + k - 1 : w), 0, 0, s0 + k) | D_NOPROC, mkfill(B[k], s0 + k)};
        cur = -1;
        for (int i = 0; i < nb; i++) {
            const Item x = B[i];
            const int k = i % NSB, slot = s0 + k;
            const uint32_t fill = i + NSB < nb ? mkfill(B[i + NSB], slot) : (uint32_t)F_NONE;
            if (x.ctx != cur && x.kind != K_RES) T.b[w][m++] = Desc{mk0(BAR_Q + x.ctx, 0, 0, slot) | D_NOPROC, F_NONE};
            cur = x.ctx;
            const uint32_t fl = (i + 1 == nb || B[i + 1].ctx != cur) ? D_FLUSH : 0u;
            const int b = x.ctx & 1;
            if (x.kind == K_RES) T.b[w][m++] = Desc{mk0(BAR_Q + x.ctx, 0, x.ctx, slot) | fl, fill};
            else if (x.kind == K_DUMP) {
                T.dumpslot[b][x.idx - NNR] = slot;
                T.b[w][m++] = Desc{mk0(BAR_DUMP + b * NRF + x.idx - NNR, 0, x.ctx, slot) | fl, fill};
            } else { T.b[w][m++] = Desc{mk0(BAR_FULL + slot, parb[k], x.ctx, slot) | fl, fill}; parb[k] ^= 1; }
        }
        T.b[w][m++] = Desc{D_END, F_NONE};
        if (m > LB) T.ok = false;
    }
    return T;
}
constexpr Tables HT = build_tables();
static_assert(HT.ok, "schedule does not fit");
constexpr unsigned long long pack_slots(const int* v) { unsigned long long r = 0; for (int i = 0; i < NRF; i++) r |= (unsigned long long)v[i] << (4 * i); return r; }
constexpr unsigned long long CAP0 = pack_slots(HT.capslot[0]), CAP1 = pack_slots(HT.capslot[1]);
constexpr unsigned long long DUMP0 = pack_slots(HT.dumpslot[0]), DUMP1 = pack_slots(HT.dumpslot[1]);
constexpr uint32_t INITA0 = HT.inita[0], INITA1 = HT.inita[1], INITA2 = HT.inita[2];
static_assert(NRF <= 16, "slot packing");
__device__ const Tables g_tab = build_tables();
constexpr uint32_t TAB_BYTES = (3 * LA + 3 * LB) * 8;
static_assert(TAB_BYTES % 16 == 0, "bulk copy size");

constexpr uint32_t SM_W = NSLOT * SLOT_B;
constexpr uint32_t SM_Q = SM_W + 3 * 8192;
constexpr uint32_t SM_PART = SM_Q + 2048;
constexpr uint32_t XS = 1040;
constexpr uint32_t SM_XN = SM_PART + 6 * 528;
constexpr uint32_t SM_BIAS = SM_XN + 2 * XS;
constexpr uint32_t SM_V = SM_BIAS + 64;
constexpr uint32_t SM_XO = SM_V + 80;
constexpr uint32_t SM_EPOCH = SM_XO + 64;
constexpr uint32_t SM_TAB = SM_XO + 80;
constexpr uint32_t SM_BAR = SM_TAB + TAB_BYTES;
constexpr uint32_t SM_TOTAL = SM_BAR + NBAR * 8;
static_assert(SM_TOTAL <= 232448 && NBAR * 8 < 2048, "shared memory budget");

constexpr int XR = 8;
__device__ __align__(128) uint32_t g_opart[4][NCTA][160];
__device__ __align__(128) uint32_t g_qpart[4][NCTA][128];
__device__ __align__(128) uint32_t g_inbox[2][32][NCTA][16];
__device__ __align__(128) uint32_t g_xrow[4][8][1024];
__device__ unsigned g_epoch;
#define TS(i) do {} while (0)
#define TSYNC(k) do {} while (0)

struct Params {
    const __nv_bfloat16 *x, *k, *v, *b1, *b2;
    __nv_bfloat16* out;
    uint32_t zero;
    CUtensorMap mwq, mwo, mw1, mw2;
};

__device__ __forceinline__ void mbar_init(uint32_t bar, int cnt) { asm volatile("mbarrier.init.shared::cta.b64 [%0], %1;" ::"r"(bar), "r"(cnt)); }
__device__ __forceinline__ void mbar_expect_tx(uint32_t bar, uint32_t bytes) { asm volatile("mbarrier.arrive.expect_tx.shared::cta.b64 _, [%0], %1;" ::"r"(bar), "r"(bytes) : "memory"); }
__device__ __forceinline__ void mbar_arrive(uint32_t bar) { asm volatile("mbarrier.arrive.shared::cta.b64 _, [%0];" ::"r"(bar) : "memory"); }
__device__ __forceinline__ void mbar_arrive_elect(uint32_t bar) {
    asm volatile("{\n.reg .pred e;\nelect.sync _|e, 0xffffffff;\n@e mbarrier.arrive.shared::cta.b64 _, [%0];\n}" ::"r"(bar) : "memory");
}
__device__ __forceinline__ bool mbar_test(uint32_t bar, uint32_t parity) {
    uint32_t ok;
    asm volatile("{\n.reg .pred p;\nmbarrier.test_wait.parity.shared::cta.b64 p, [%1], %2;\nselp.u32 %0, 1, 0, p;\n}" : "=r"(ok) : "r"(bar), "r"(parity) : "memory");
    return ok;
}
__device__ __forceinline__ bool mbar_try(uint32_t bar, uint32_t parity) {
    uint32_t ok;
    asm volatile("{\n.reg .pred p;\nmbarrier.try_wait.parity.shared::cta.b64 p, [%1], %2;\nselp.u32 %0, 1, 0, p;\n}" : "=r"(ok) : "r"(bar), "r"(parity) : "memory");
    return ok;
}
__device__ __forceinline__ void mbar_wait(uint32_t bar, uint32_t parity) {
    uint32_t it = 0;
    while (!__all_sync(0xffffffffu, mbar_try(bar, parity))) { if (++it > (1u << 24)) __trap(); }
}
__device__ __forceinline__ void mbar_wait_long(uint32_t bar) {
    uint32_t it = 0, ok;
    do {
        asm volatile("{\n.reg .pred p;\nmbarrier.try_wait.parity.shared::cta.b64 p, [%1], 0, %2;\nselp.u32 %0, 1, 0, p;\n}" : "=r"(ok) : "r"(bar), "r"(2000u) : "memory");
        if (++it > (1u << 22)) __trap();
    } while (!__all_sync(0xffffffffu, ok));
}
__device__ __forceinline__ bool elect_one() {
    uint32_t r;
    asm volatile("{\n.reg .pred P;\nelect.sync _|P, 0xffffffff;\nselp.b32 %0, 1, 0, P;\n}" : "=r"(r));
    return r;
}
__device__ __forceinline__ bool mbar_test_warp(uint32_t bar, uint32_t parity) { return __all_sync(0xffffffffu, mbar_test(bar, parity)); }
__device__ __forceinline__ void bulk_g2s(uint32_t dst, const void* src, uint32_t bytes, uint32_t bar, uint64_t pol) {
    asm volatile("cp.async.bulk.shared::cluster.global.mbarrier::complete_tx::bytes.L2::cache_hint [%0], [%1], %2, [%3], %4;"
                 ::"r"(dst), "l"(src), "r"(bytes), "r"(bar), "l"(pol) : "memory");
}
__device__ __forceinline__ void half_fill(bool cond, bool arm, bool keep, uint32_t dst, const void* src, uint32_t bar, uint64_t pol, uint32_t zero) {
    asm volatile("{\n.reg .pred e, a, k;\n.reg .b32 t;\nelect.sync _|e, 0xffffffff;\nsetp.ne.and.u32 e, %0, 0, e;\nsetp.ne.and.u32 a, %1, 0, e;\n"
                 "@a mbarrier.arrive.expect_tx.shared::cta.b64 _, [%5], 16384;\n"
                 "@e cp.async.bulk.shared::cluster.global.mbarrier::complete_tx::bytes.L2::cache_hint [%3], [%4], 8192, [%5], %6;\n"
                 "ld.volatile.shared.u32 t, [%3];\nand.b32 t, t, %7;\nor.b32 t, t, %2;\nsetp.ne.and.u32 k, t, 0, e;\n"
                 "@k cp.async.bulk.prefetch.L2.global [%4], 8192;\n}"
                 ::"r"((uint32_t)cond), "r"((uint32_t)arm), "r"((uint32_t)keep), "r"(dst), "l"(src), "r"(bar), "l"(pol), "r"(zero) : "memory");
}
__device__ __forceinline__ void ldsm4(uint32_t (&r)[4], uint32_t a) {
    asm volatile("ldmatrix.sync.aligned.m8n8.x4.shared.b16 {%0,%1,%2,%3}, [%4];" : "=r"(r[0]), "=r"(r[1]), "=r"(r[2]), "=r"(r[3]) : "r"(a));
}
__device__ __forceinline__ void ldsm4t(uint32_t (&r)[4], uint32_t a) {
    asm volatile("ldmatrix.sync.aligned.m8n8.x4.trans.shared.b16 {%0,%1,%2,%3}, [%4];" : "=r"(r[0]), "=r"(r[1]), "=r"(r[2]), "=r"(r[3]) : "r"(a));
}
__device__ __forceinline__ void mma16816(float (&c)[4], const uint32_t (&a)[4], uint32_t b0, uint32_t b1) {
    asm volatile("mma.sync.aligned.m16n8k16.row.col.f32.bf16.bf16.f32 {%0,%1,%2,%3}, {%4,%5,%6,%7}, {%8,%9}, {%0,%1,%2,%3};"
                 : "+f"(c[0]), "+f"(c[1]), "+f"(c[2]), "+f"(c[3]) : "r"(a[0]), "r"(a[1]), "r"(a[2]), "r"(a[3]), "r"(b0), "r"(b1));
}
__device__ __forceinline__ void lds128(uint32_t* r, uint32_t a) {
    asm volatile("ld.shared.v4.u32 {%0,%1,%2,%3}, [%4];" : "=r"(r[0]), "=r"(r[1]), "=r"(r[2]), "=r"(r[3]) : "r"(a) : "memory");
}
__device__ __forceinline__ void sts128(uint32_t a, const uint32_t* r) {
    asm volatile("st.shared.v4.u32 [%0], {%1,%2,%3,%4};" ::"r"(a), "r"(r[0]), "r"(r[1]), "r"(r[2]), "r"(r[3]) : "memory");
}
__device__ __forceinline__ uint32_t lds32(uint32_t a) { uint32_t r; asm volatile("ld.shared.u32 %0, [%1];" : "=r"(r) : "r"(a) : "memory"); return r; }
__device__ __forceinline__ uint32_t lds16(uint32_t a) { uint16_t r; asm volatile("ld.shared.u16 %0, [%1];" : "=h"(r) : "r"(a) : "memory"); return r; }
__device__ __forceinline__ float ldsf(uint32_t a) { float r; asm volatile("ld.shared.f32 %0, [%1];" : "=f"(r) : "r"(a) : "memory"); return r; }
__device__ __forceinline__ void sts32(uint32_t a, uint32_t v) { asm volatile("st.shared.u32 [%0], %1;" ::"r"(a), "r"(v) : "memory"); }
__device__ __forceinline__ void sts16(uint32_t a, uint32_t v) { asm volatile("st.shared.u16 [%0], %1;" ::"r"(a), "h"((uint16_t)v) : "memory"); }
__device__ __forceinline__ void stsf(uint32_t a, float v) { asm volatile("st.shared.f32 [%0], %1;" ::"r"(a), "f"(v) : "memory"); }
__device__ __forceinline__ void sts64(uint32_t a, uint32_t v0, uint32_t v1) { asm volatile("st.shared.v2.u32 [%0], {%1,%2};" ::"r"(a), "r"(v0), "r"(v1) : "memory"); }
__device__ __forceinline__ void cp16(uint32_t dst, const void* src) { asm volatile("cp.async.cg.shared.global [%0], [%1], 16;" ::"r"(dst), "l"(src) : "memory"); }
__device__ __forceinline__ float ex2(float x) { float r; asm("ex2.approx.ftz.f32 %0, %1;" : "=f"(r) : "f"(x)); return r; }
__device__ __forceinline__ uint32_t pack_bf16(float lo, float hi) { uint32_t r; asm("cvt.rn.bf16x2.f32 %0, %1, %2;" : "=r"(r) : "f"(hi), "f"(lo)); return r; }
__device__ __forceinline__ float bf_lo(uint32_t v) { return __uint_as_float(v << 16); }
__device__ __forceinline__ float bf_hi(uint32_t v) { return __uint_as_float(v & 0xffff0000u); }
__device__ __forceinline__ float bfr(float x) { return __bfloat162float(__float2bfloat16_rn(x)); }
__device__ __forceinline__ uint32_t ll_pack(float v, uint32_t tag) { return (__float_as_uint(v) & ~15u) | tag; }
__device__ __forceinline__ float ll_val(uint32_t w) { return __uint_as_float(w & ~15u); }
__device__ __forceinline__ void st_w(uint32_t* p, uint32_t w) { asm volatile("st.relaxed.gpu.global.u32 [%0], %1;" ::"l"(p), "r"(w) : "memory"); }
__device__ __forceinline__ void st_w4(uint32_t* p, uint32_t a, uint32_t b, uint32_t c, uint32_t d) {
    asm volatile("st.relaxed.gpu.global.v4.u32 [%0], {%1,%2,%3,%4};" ::"l"(p), "r"(a), "r"(b), "r"(c), "r"(d) : "memory");
}
__device__ __forceinline__ void ll_store(uint32_t* p, float v, uint32_t tag) { st_w(p, ll_pack(v, tag)); }
__device__ __forceinline__ void ld_w4(const uint32_t* p, bool pred, uint32_t (&w)[4]) {
    asm volatile("{\n.reg .pred q;\nsetp.ne.u32 q, %5, 0;\n@q ld.relaxed.gpu.global.v4.u32 {%0,%1,%2,%3}, [%4];\n}"
                 : "+r"(w[0]), "+r"(w[1]), "+r"(w[2]), "+r"(w[3]) : "l"(p), "r"((uint32_t)pred) : "memory");
}
__device__ __forceinline__ void ld_w2(const uint32_t* p, bool pred, uint32_t& a, uint32_t& b) {
    asm volatile("{\n.reg .pred q;\nsetp.ne.u32 q, %3, 0;\n@q ld.relaxed.gpu.global.v2.u32 {%0,%1}, [%2];\n}" : "+r"(a), "+r"(b) : "l"(p), "r"((uint32_t)pred) : "memory");
}
__device__ __forceinline__ void ld_w1(const uint32_t* p, bool pred, uint32_t& a) {
    asm volatile("{\n.reg .pred q;\nsetp.ne.u32 q, %2, 0;\n@q ld.relaxed.gpu.global.u32 %0, [%1];\n}" : "+r"(a) : "l"(p), "r"((uint32_t)pred) : "memory");
}
__device__ __forceinline__ bool miss4(const uint32_t (&w)[4], uint32_t tag) { return (((w[0] ^ tag) | (w[1] ^ tag) | (w[2] ^ tag) | (w[3] ^ tag)) & 15u) != 0; }
#define SPIN_GUARD(it) do { if (++(it) > (1u << 22)) __trap(); } while (0)

struct PVB { uint32_t x0, x1, y0, y1; };
struct LaneC {
    int g, t, v;
    int src0, src1;
    uint32_t sx0, sy0;
    uint32_t voff;
    int vrow;
};
__device__ __forceinline__ PVB spread(uint32_t pk, const LaneC& L) {
    uint32_t v0 = __shfl_sync(0xffffffffu, pk, L.src0), v1 = __shfl_sync(0xffffffffu, pk, L.src1);
    PVB b;
    b.x0 = __byte_perm(v0, 0, L.sx0); b.y0 = __byte_perm(v0, 0, L.sy0);
    b.x1 = __byte_perm(v1, 0, L.sx0 ^ 0x5454u); b.y1 = __byte_perm(v1, 0, L.sy0 ^ 0x7676u);
    return b;
}
__device__ __forceinline__ void pv_load(uint32_t (&a)[8][4], uint32_t base) {
#pragma unroll
    for (int c = 0; c < 8; c++) ldsm4t(a[c], base ^ (c << 4));
}
template <int U> __device__ __forceinline__ void raw_load(uint32_t (&r)[16], uint32_t a) {
    asm volatile("ld.shared.v4.u32 {%0,%1,%2,%3}, [%16];\nld.shared.v4.u32 {%4,%5,%6,%7}, [%16+512];\n"
                 "ld.shared.v4.u32 {%8,%9,%10,%11}, [%16+1024];\nld.shared.v4.u32 {%12,%13,%14,%15}, [%16+1536];\nmembar.cta; // %17"
                 : "=r"(r[0]), "=r"(r[1]), "=r"(r[2]), "=r"(r[3]), "=r"(r[4]), "=r"(r[5]), "=r"(r[6]), "=r"(r[7]), "=r"(r[8]), "=r"(r[9]),
                   "=r"(r[10]), "=r"(r[11]), "=r"(r[12]), "=r"(r[13]), "=r"(r[14]), "=r"(r[15]) : "r"(a), "n"(U) : "memory");
}
template <int U> __device__ __forceinline__ void raw_store(const uint32_t (&r)[16], uint32_t a) {
    asm volatile("st.shared.v4.u32 [%16], {%0,%1,%2,%3};\nst.shared.v4.u32 [%16+512], {%4,%5,%6,%7};\n"
                 "st.shared.v4.u32 [%16+1024], {%8,%9,%10,%11};\nst.shared.v4.u32 [%16+1536], {%12,%13,%14,%15};\nfence.proxy.async.shared::cta; // %17"
                 :: "r"(r[0]), "r"(r[1]), "r"(r[2]), "r"(r[3]), "r"(r[4]), "r"(r[5]), "r"(r[6]), "r"(r[7]), "r"(r[8]), "r"(r[9]),
                    "r"(r[10]), "r"(r[11]), "r"(r[12]), "r"(r[13]), "r"(r[14]), "r"(r[15]), "r"(a), "n"(U) : "memory");
}
template <int LO, int HI, bool LOAD> __device__ __forceinline__ void raw_dispatch(uint32_t (&r)[NRF][16], int u, uint32_t a) {
    if constexpr (HI - LO == 1) {
        if constexpr (LOAD) raw_load<LO>(r[LO], a); else raw_store<LO>(r[LO], a);
    } else {
        constexpr int MID = (LO + HI) / 2;
        if (u < MID) raw_dispatch<LO, MID, LOAD>(r, u, a); else raw_dispatch<MID, HI, LOAD>(r, u, a);
    }
}

struct Ctx { float o[4]; float m, l; };
constexpr float SCL = 0.08838834764831845f * 1.4426950408889634f;

__device__ __forceinline__ void process_tile(Ctx& S, uint32_t tile, uint32_t qaddr, uint32_t koff, uint32_t voff, const LaneC& L,
                                             uint32_t fill, uint32_t bars, const Params& p, uint64_t pol) {
    float sa0[4] = {0.f, 0.f, 0.f, 0.f}, sa1[4] = {0.f, 0.f, 0.f, 0.f}, sb0[4] = {0.f, 0.f, 0.f, 0.f}, sb1[4] = {0.f, 0.f, 0.f, 0.f};
    const uint32_t kb = tile + koff;
    {
        uint32_t q[4][4], a[4][4][4];
#pragma unroll
        for (int i = 0; i < 4; i++) {
            lds128(q[i], qaddr ^ (i << 4));
            const uint32_t k0 = kb ^ ((2 * i) << 5), k1 = kb ^ ((2 * i + 1) << 5);
            ldsm4(a[i][0], k0); ldsm4(a[i][1], k1); ldsm4(a[i][2], k0 + 4096); ldsm4(a[i][3], k1 + 4096);
            if (i > 0) {
                mma16816(sa0, a[i - 1][0], q[i - 1][0], q[i - 1][1]); mma16816(sa1, a[i - 1][1], q[i - 1][2], q[i - 1][3]);
                mma16816(sb0, a[i - 1][2], q[i - 1][0], q[i - 1][1]); mma16816(sb1, a[i - 1][3], q[i - 1][2], q[i - 1][3]);
            }
        }
        mma16816(sa0, a[3][0], q[3][0], q[3][1]); mma16816(sa1, a[3][1], q[3][2], q[3][3]);
        mma16816(sb0, a[3][2], q[3][0], q[3][1]); mma16816(sb1, a[3][3], q[3][2], q[3][3]);
    }
    const uint32_t vb = tile + voff;
    uint32_t av[8][4];
    pv_load(av, vb);
    const bool refill = ((fill & 7) - 1u) < 2u;
    const uint32_t fbar = bars + ((fill >> 4) & 0x7ff);
    const size_t foff = ((size_t)blockIdx.x << 19) + ((fill >> 16) << 13);
    if (fill & F_NORM) asm("createpolicy.fractional.L2::evict_normal.b64 %0, 1.0;" : "=l"(pol));
    const char* kbase = reinterpret_cast<const char*>(p.k);
    const char* vbase = reinterpret_cast<const char*>(p.v);
    half_fill(refill, true, fill & 2, tile, kbase + foff, fbar, pol, p.zero);
    const bool odd = L.g & 1;
    const bool valid = (L.v == 0);
    const float s0 = (odd ? sa0[1] + sa1[1] : sa0[0] + sa1[0]) * SCL, s1 = (odd ? sa0[3] + sa1[3] : sa0[2] + sa1[2]) * SCL;
    const float s2 = (odd ? sb0[1] + sb1[1] : sb0[0] + sb1[0]) * SCL, s3 = (odd ? sb0[3] + sb1[3] : sb0[2] + sb1[2]) * SCL;
    float mx = valid ? fmaxf(fmaxf(s0, s1), fmaxf(s2, s3)) : -INFINITY;
    if (__any_sync(0xffffffffu, mx > S.m)) {
#pragma unroll
        for (int o = 16; o > 0; o >>= 1) mx = fmaxf(mx, __shfl_xor_sync(0xffffffffu, mx, o));
        const float f = ex2(S.m - mx);
        S.o[0] *= f; S.o[1] *= f; S.o[2] *= f; S.o[3] *= f; S.l *= f;
        S.m = mx;
    }
    const float p0 = ex2(s0 - S.m), p1 = ex2(s1 - S.m), p2 = ex2(s2 - S.m), p3 = ex2(s3 - S.m);
    if (valid) S.l += (p0 + p1) + (p2 + p3);
    const PVB ba = spread(pack_bf16(p0, p1), L), bb = spread(pack_bf16(p2, p3), L);
    float o1[4] = {0.f, 0.f, 0.f, 0.f}, o2[4] = {0.f, 0.f, 0.f, 0.f}, o3[4] = {0.f, 0.f, 0.f, 0.f};
#pragma unroll
    for (int c = 0; c < 8; c += 2) {
        const bool on = (L.v == (c >> 1));
        uint32_t w0[4], w1[4];
        ldsm4t(w0, (vb ^ (c << 4)) + 4096); ldsm4t(w1, (vb ^ ((c + 1) << 4)) + 4096);
        mma16816(S.o, av[c], on ? ba.x0 : 0u, on ? ba.y0 : 0u);
        mma16816(o1, av[c + 1], on ? ba.x1 : 0u, on ? ba.y1 : 0u);
        mma16816(o2, w0, on ? bb.x0 : 0u, on ? bb.y0 : 0u);
        mma16816(o3, w1, on ? bb.x1 : 0u, on ? bb.y1 : 0u);
    }
    half_fill(refill, false, fill & 2, tile + HALF_B, vbase + foff, fbar, pol, p.zero);
    S.o[0] += o1[0] + (o2[0] + o3[0]); S.o[1] += o1[1] + (o2[1] + o3[1]);
    S.o[2] += o1[2] + (o2[2] + o3[2]); S.o[3] += o1[3] + (o2[3] + o3[3]);
}

__device__ __forceinline__ void flush_ctx(Ctx& S, uint32_t part, bool first, int lane, const LaneC& L) {
    float l = S.l;
#pragma unroll
    for (int o = 16; o > 0; o >>= 1) l += __shfl_xor_sync(0xffffffffu, l, o);
    const uint32_t a = part + (16 * L.t + L.g) * 4;
    float m = S.m;
    if (!first) {
        const float mo = ldsf(part + 512), lo = ldsf(part + 516);
        m = fmaxf(mo, S.m);
        const float fo = ex2(mo - m), fn = ex2(S.m - m);
        S.o[0] = S.o[0] * fn + ldsf(a) * fo; S.o[1] = S.o[1] * fn + ldsf(a + 32) * fo;
        S.o[2] = S.o[2] * fn + ldsf(a + 256) * fo; S.o[3] = S.o[3] * fn + ldsf(a + 288) * fo;
        l = l * fn + lo * fo;
        __syncwarp();
    }
    stsf(a, S.o[0]); stsf(a + 32, S.o[1]); stsf(a + 256, S.o[2]); stsf(a + 288, S.o[3]);
    if (lane == 0) { stsf(part + 512, m); stsf(part + 516, l); }
    S.o[0] = S.o[1] = S.o[2] = S.o[3] = 0.f; S.l = 0.f; S.m = -INFINITY;
    __syncwarp();
}

template <bool PF> __device__ __forceinline__ void tma2d(uint32_t dst, const CUtensorMap* map, int c0, int c1, uint32_t bar, uint64_t pol) {
    if (PF) asm volatile("cp.async.bulk.prefetch.tensor.2d.L2.global.tile [%0, {%1, %2}];" ::"l"(map), "r"(c0), "r"(c1) : "memory");
    else asm volatile("cp.async.bulk.tensor.2d.shared::cluster.global.tile.mbarrier::complete_tx::bytes.L2::cache_hint [%0], [%1, {%2, %3}], [%4], %5;"
                      ::"r"(dst), "l"(map), "r"(c0), "r"(c1), "r"(bar), "l"(pol) : "memory");
}
template <int ST, int I, bool PF> __device__ __forceinline__ void load_chunk(const Params& p, uint32_t dst, uint32_t bar, uint64_t pol) {
    const int cta = blockIdx.x;
    if (ST == 0) {
        tma2d<PF>(dst, &p.mwo, 128 * I, 32 * cta, bar, pol); tma2d<PF>(dst + 4096, &p.mwo, 128 * I + 64, 32 * cta, bar, pol);
    } else if (ST == 1 && I < 2) {
        tma2d<PF>(dst, &p.mw1, 16 * cta, 256 * I, bar, pol);
    } else if (ST == 1) {
#pragma unroll
        for (int i = 0; i < 4; i++) tma2d<PF>(dst + i * 2048, &p.mw2, 256 * (I - 2) + 64 * i, 16 * cta, bar, pol);
    } else {
        tma2d<PF>(dst, &p.mwq, 128 * (cta >> 2) + 32 * I, 128 * (cta & 3), bar, pol);
    }
}
struct WBuf {
    uint32_t a[3], bar, par;
    __device__ __forceinline__ void wait3() { mbar_wait(bar, par); }
    __device__ __forceinline__ void wait4() { mbar_wait(bar + 8, par); }
    __device__ __forceinline__ void rotate() { const uint32_t x = a[0]; a[0] = a[1]; a[1] = a[2]; a[2] = x; par ^= 1; }
};
template <int ST, bool PF4> __device__ __forceinline__ void load_stage1(const Params& p, const WBuf& W, uint64_t pol) {
    if (ST == 1 && blockIdx.x >= NMLP) { mbar_arrive(W.bar); mbar_arrive(W.bar + 8); return; }
    mbar_expect_tx(W.bar, 3 * 8192);
    load_chunk<ST, 0, false>(p, W.a[0], W.bar, pol);
    load_chunk<ST, 1, false>(p, W.a[1], W.bar, pol);
    load_chunk<ST, 2, false>(p, W.a[2], W.bar, pol);
    if (PF4) load_chunk<ST, 3, true>(p, 0, 0, pol);
}
template <int ST, bool PF4> __device__ __forceinline__ void load_stage(const Params& p, const WBuf& W, uint64_t pol) {
    __syncwarp();
    if (elect_one()) load_stage1<ST, PF4>(p, W, pol);
    __syncwarp();
}
template <int ST> __device__ __forceinline__ void load_fourth(const Params& p, const WBuf& W, uint64_t pol) {
    __syncwarp();
    if (elect_one()) { mbar_expect_tx(W.bar + 8, 8192); load_chunk<ST, 3, false>(p, W.a[0], W.bar + 8, pol); }
    __syncwarp();
}
__device__ __forceinline__ void frag8(uint32_t (&f)[8][4], uint32_t a) {
#pragma unroll
    for (int u = 0; u < 4; u++) { ldsm4t(f[u], a ^ (u << 5)); ldsm4t(f[4 + u], (a ^ (u << 5)) + 2048); }
}
template <int N, int STRIDE, int HALF> __device__ __forceinline__ void ll_gather(const uint32_t* src, int n, uint32_t tag, uint32_t (&w)[N][4]) {
#pragma unroll
    for (int i = 0; i < N; i++) w[i][0] = w[i][1] = w[i][2] = w[i][3] = i < n ? 0u : tag;
    uint32_t it = 0;
    while (true) {
#pragma unroll
        for (int i = 0; i < N; i++) ld_w4(src + (HALF ? (i & 3) * STRIDE + (i >> 2) * HALF : i * STRIDE), miss4(w[i], tag), w[i]);
        bool miss = false;
#pragma unroll
        for (int i = 0; i < N; i++) miss |= miss4(w[i], tag);
        if (!__any_sync(0xffffffffu, miss)) break;
        SPIN_GUARD(it);
    }
}
__device__ __forceinline__ void pick4(float (&o)[4], const float (&a0)[4], const float (&a1)[4], const float (&a2)[4], const float (&a3)[4], int t) {
#pragma unroll
    for (int i = 0; i < 4; i++) o[i] = (t & 2) ? ((t & 1) ? a3[i] : a2[i]) : ((t & 1) ? a1[i] : a0[i]);
}
template <bool COLL> __device__ __forceinline__ void issue_fill(uint32_t fill, uint32_t dst, uint32_t bars, const Params& p, uint64_t pol) {
    const uint32_t fbar = bars + ((fill >> 4) & 0x7ff);
    const size_t foff = ((size_t)blockIdx.x << 19) + ((fill >> 16) << 13);
    if (fill & F_NORM) asm("createpolicy.fractional.L2::evict_normal.b64 %0, 1.0;" : "=l"(pol));
    const char* kbase = reinterpret_cast<const char*>(p.k);
    const char* vbase = reinterpret_cast<const char*>(p.v);
    if (COLL) {
        half_fill(true, true, fill & 2, dst, kbase + foff, fbar, pol, p.zero);
        half_fill(true, false, fill & 2, dst + HALF_B, vbase + foff, fbar, pol, p.zero);
    } else {
        mbar_expect_tx(fbar, SLOT_B);
        bulk_g2s(dst, kbase + foff, HALF_B, fbar, pol);
        bulk_g2s(dst + HALF_B, vbase + foff, HALF_B, fbar, pol);
    }
}
__device__ __forceinline__ uint2 lds64(uint32_t a) {
    uint2 r;
    asm volatile("ld.shared.v2.u32 {%0,%1}, [%2];" : "=r"(r.x), "=r"(r.y) : "r"(a) : "memory");
    return r;
}
__device__ __forceinline__ uint2 uniform2(uint2 r) {
    r.x = __shfl_sync(0xffffffffu, r.x, 0); r.y = __shfl_sync(0xffffffffu, r.y, 0);
    return r;
}

__device__ __forceinline__ float gelu_tanh(float x) {
    const float u = 0.7978845608028654f * (x + 0.044715f * x * x * x);
    const float th = 1.f - 2.f / (__expf(2.f * u) + 1.f);
    return 0.5f * x * (1.f + th);
}

template <int NB> __device__ __forceinline__ void gather_o(const uint32_t* src, int lane_off, uint32_t tag, bool live, float (&o)[NB]) {
    uint32_t wm[4 * NB], wl[4 * NB], wo[4 * NB];
#pragma unroll
    for (int i = 0; i < 4 * NB; i++) wm[i] = wl[i] = wo[i] = live ? 0u : tag;
    uint32_t it = 0;
    while (true) {
#pragma unroll
        for (int i = 0; i < 4 * NB; i++) {
            const uint32_t* q = src + (i >> 2) * (NCTA * 160) + (i & 3) * 160;
            ld_w2(q + 128, (((wm[i] ^ tag) | (wl[i] ^ tag)) & 15u) != 0, wm[i], wl[i]);
            ld_w1(q + lane_off, ((wo[i] ^ tag) & 15u) != 0, wo[i]);
        }
        uint32_t miss = 0;
#pragma unroll
        for (int i = 0; i < 4 * NB; i++) miss |= (wm[i] ^ tag) | (wl[i] ^ tag) | (wo[i] ^ tag);
        if (!__any_sync(0xffffffffu, (miss & 15u) != 0)) break;
        SPIN_GUARD(it);
    }
#pragma unroll
    for (int b = 0; b < NB; b++) {
        const float M = fmaxf(fmaxf(ll_val(wm[4 * b]), ll_val(wm[4 * b + 1])), fmaxf(ll_val(wm[4 * b + 2]), ll_val(wm[4 * b + 3])));
        float Ls = 0.f, O = 0.f;
#pragma unroll
        for (int i = 4 * b; i < 4 * b + 4; i++) { const float f = ex2(ll_val(wm[i]) - M); Ls += ll_val(wl[i]) * f; O += ll_val(wo[i]) * f; }
        o[b] = O / Ls;
    }
}
__device__ __forceinline__ void bar256() { asm volatile("bar.sync 1, 256;" ::: "memory"); }
__device__ __forceinline__ void red_sf(uint32_t a, float v) { asm volatile("red.shared.add.f32 [%0], %1;" ::"r"(a), "f"(v) : "memory"); }
__device__ __forceinline__ void fill_ones(uint32_t a, int lane) {
    const uint32_t o[4] = {0x3f803f80u, 0x3f803f80u, 0x3f803f80u, 0x3f803f80u};
    sts128(a + lane * 16, o); sts128(a + 512 + lane * 16, o);
}
__device__ __forceinline__ void ln_store2(const float (&x)[2][16], uint32_t xn, int lane) {
    float s[2] = {0.f, 0.f}, q[2] = {0.f, 0.f};
#pragma unroll
    for (int i = 0; i < 32; i++) s[i >> 4] += x[i >> 4][i & 15];
#pragma unroll
    for (int o = 16; o > 0; o >>= 1) { s[0] += __shfl_xor_sync(0xffffffffu, s[0], o); s[1] += __shfl_xor_sync(0xffffffffu, s[1], o); }
    s[0] *= (1.f / DM); s[1] *= (1.f / DM);
#pragma unroll
    for (int i = 0; i < 32; i++) { const float d = x[i >> 4][i & 15] - s[i >> 4]; q[i >> 4] += d * d; }
#pragma unroll
    for (int o = 16; o > 0; o >>= 1) { q[0] += __shfl_xor_sync(0xffffffffu, q[0], o); q[1] += __shfl_xor_sync(0xffffffffu, q[1], o); }
#pragma unroll
    for (int b = 0; b < 2; b++) {
        const float r = rsqrtf(q[b] * (1.f / DM) + 1e-5f), mean = s[b];
#pragma unroll
        for (int i = 0; i < 4; i++)
            sts64(xn + b * XS + (128 * i + 4 * lane) * 2, pack_bf16((x[b][4 * i] - mean) * r, (x[b][4 * i + 1] - mean) * r),
                  pack_bf16((x[b][4 * i + 2] - mean) * r, (x[b][4 * i + 3] - mean) * r));
    }
}

__global__ void __launch_bounds__(384, 1) fused_kernel(const __grid_constant__ Params p) {
    extern __shared__ __align__(1024) unsigned char smem_raw[];
    const uint32_t sb = (uint32_t)__cvta_generic_to_shared(smem_raw);
    const int tid = threadIdx.x, lane = tid & 31;
    const int warp = __shfl_sync(0xffffffffu, tid >> 5, 0);
    const int cta = blockIdx.x;

    const uint32_t bars = sb + SM_BAR;
    if (tid == 0) TSYNC(0);
    uint64_t pol;
    asm volatile("createpolicy.fractional.L2::evict_first.b64 %0, 1.0;" : "=l"(pol));
    WBuf W;
    W.a[0] = sb + SM_W; W.a[1] = sb + SM_W + 8192; W.a[2] = sb + SM_W + 16384; W.bar = bars + BAR_W * 8; W.par = 0;
    if (warp == 0) {
        if (elect_one()) {
#pragma unroll
            for (int k = 0; k < 3; k++) mbar_init(bars + (BAR_FULL + k) * 8, 1);
            mbar_init(bars + BAR_TAB * 8, 1);
            asm volatile("fence.mbarrier_init.release.cluster;" ::: "memory");
            mbar_expect_tx(bars + BAR_TAB * 8, TAB_BYTES);
            asm volatile("cp.async.bulk.shared::cluster.global.mbarrier::complete_tx::bytes [%0], [%1], %2, [%3];"
                         ::"r"(sb + SM_TAB), "l"(&g_tab), "r"(TAB_BYTES), "r"(bars + BAR_TAB * 8) : "memory");
            issue_fill<false>(INITA0, sb, bars, p, pol);
            issue_fill<false>(INITA1, sb + SLOT_B, bars, p, pol);
            issue_fill<false>(INITA2, sb + 2 * SLOT_B, bars, p, pol);
        }
    } else if (warp == 3) {
#pragma unroll
        for (int i = 0; i < 4; i++) cp16(sb + SM_XN + (i >> 1) * XS + (i & 1) * 512 + lane * 16, p.x + 256 * i + 8 * lane);
        if (lane < 2) cp16(sb + SM_BIAS + lane * 16, p.b2 + 16 * (cta & 31) + 8 * lane);
        else if (lane < 4 && cta < NMLP) cp16(sb + SM_BIAS + lane * 16, p.b1 + 16 * cta + 8 * (lane - 2));
        else if (lane == 4) asm volatile("cp.async.ca.shared.global [%0], [%1], 4;" ::"r"(sb + SM_EPOCH), "l"(&g_epoch) : "memory");
        if (elect_one()) {
            asm volatile("prefetch.tensormap [%0];" ::"l"(&p.mwq) : "memory");
            mbar_init(W.bar, 1); mbar_init(W.bar + 8, 1);
            asm volatile("fence.mbarrier_init.release.cluster;" ::: "memory");
            load_stage1<2, true>(p, W, pol);
        }
    } else if (warp >= 4) {
        if (elect_one()) {
            for (int i = warp - 1; i < NBAR; i += 8) {
                if (i == BAR_TAB || i == BAR_W || i == BAR_W + 1) continue;
                int cnt = 1;
                if ((i >= BAR_CAP && i < BAR_FREE) || (i >= BAR_DUMP && i < BAR_Q)) cnt = 8;
                if (i >= BAR_CTX && i < BAR_TAB) cnt = 6;
                mbar_init(bars + i * 8, cnt);
            }
            asm volatile("fence.mbarrier_init.release.cluster;" ::: "memory");
        }
    }
    static_assert(NBAR <= 256, "set-up mapping");
    __syncthreads();

    if (warp >= 4) {
        asm volatile("setmaxnreg.inc.sync.aligned.u32 %0;" ::"n"(REG_HI));
        const uint32_t mine = sb + (tid - 128) * 16 + ((tid >> 5) - 4) * (2048 - 512);
        uint32_t r[NRF][16];
#pragma unroll
        for (int u = 0; u < NRF; u++)
#pragma unroll
            for (int c = 0; c < 16; c++) r[u][c] = 0;
        int nc = 0, nd = 0, uc = 0, ud = 0;
        unsigned long long cs = CAP0, ds = DUMP0;
        uint32_t it = 0;
        while (nd < 2 * NRF) {
            const bool canD = nd < nc, canC = nc < 2 * NRF && nc < nd + NRF;
            const uint32_t bd = bars + (BAR_FREE + nd) * 8, bc = bars + (BAR_RF + nc) * 8;
            if (!canC) mbar_wait_long(bd);
            if (!canD) mbar_wait_long(bc);
            if (canC && mbar_test_warp(bc, 0)) {
                const uint32_t a = mine + (uint32_t)(cs & 15) * SLOT_B;
                raw_dispatch<0, NRF, true>(r, uc, a);
                __syncwarp();
                mbar_arrive_elect(bc + (BAR_CAP - BAR_RF) * 8);
                nc++; cs >>= 4;
                if (++uc == NRF) { uc = 0; cs = CAP1; }
                it = 0;
            } else if (canD && mbar_test_warp(bd, 0)) {
                const uint32_t a = mine + (uint32_t)(ds & 15) * SLOT_B;
                raw_dispatch<0, NRF, false>(r, ud, a);
                __syncwarp();
                mbar_arrive_elect(bd + (BAR_DUMP - BAR_FREE) * 8);
                nd++; ds >>= 4;
                if (++ud == NRF) { ud = 0; ds = DUMP1; }
                it = 0;
            } else {
                __nanosleep(200);
                if (++it > (1u << 24)) __trap();
            }
        }
        {
            const int sw = __shfl_sync(0xffffffffu, (threadIdx.x >> 5) - 4, 0), g = lane >> 2, t = lane & 3;
            const int vrow = (lane & 7) + 8 * (lane >> 4);
            const uint32_t aoff = vrow * 128 + ((((lane >> 3) & 1) ^ (lane & 7)) << 4);
            const uint32_t wb = sb + SM_W, wbar = bars + BAR_W * 8;
            const bool mlp = cta < NMLP, owner = cta >= 64;
            const int ob = cta >= 96 ? 0 : 1, oo = cta & 31;
            uint32_t fo[8][4], f1[4][4], f2[4][4];
            mbar_wait(wbar, 1);
            if (sw < 6) frag8(fo, wb + (((sw >> 1) + 1) % 3) * 8192 + aoff + (sw & 1) * 4096);
            bar256();
            if (tid == 128) { mbar_expect_tx(wbar, 8192); load_chunk<0, 3, false>(p, wb, wbar, pol); }
            mbar_wait(wbar, 0);
            if (sw >= 6) frag8(fo, wb + aoff + (sw & 1) * 4096);
            bar256();
            const uint32_t my = wb + sw * 1024, redH = wb + 8192, redO = wb + 8192 + 512;
            if (lane < 4) sts32(my + 160 + lane * 4, 0x3f803f80u);
            const uint32_t vb = my + (lane & 1) * 80 + (lane >> 3) * 16;
            const uint32_t xb = (lane & 2) ? my + 160 : my + 256 + (lane & 1) * 144 + (lane >> 3) * 16;
            const uint32_t xs = (lane & 2) ? 0 : 64;
            const uint32_t epoch = lds32(sb + SM_EPOCH);
            const uint32_t tag0 = epoch % 15u + 1u, tagA = ((epoch % 15u) * 6u + 6u) % 15u + 1u, tagB = ((epoch % 15u) * 6u + 7u) % 15u + 1u;
            const float bias = mlp ? bf_lo(lds16(sb + SM_BIAS + 32 + (g + 4 * (t & 2)) * 2)) : 0.f;
            uint32_t* const outbox = &g_inbox[0][4 * sw + t][cta][g];
            constexpr int OB = 32 * NCTA * 16;
            mbar_wait_long(bars + (BAR_PRE + 3) * 8);
#pragma unroll 1
            for (int pass = 0; pass < 2; pass++) {
                const bool live = pass;
                const uint32_t keep = live ? 0xffffffffu : 0u;
                auto send4 = [&](const float (&acc)[4][4], uint32_t tag) {
                    float o[4];
                    pick4(o, acc[0], acc[1], acc[2], acc[3], t);
                    st_w(outbox, ll_pack(o[0], tag) & keep); st_w(outbox + 8, ll_pack(o[2], tag) & keep);
                    st_w(outbox + OB, ll_pack(o[1], tag) & keep); st_w(outbox + OB + 8, ll_pack(o[3], tag) & keep);
                };
                auto own = [&](int st, uint32_t tag) {
                    uint32_t w[2][4];
                    ll_gather<2, 128, 0>(&g_inbox[ob][oo][0][0] + sw * 256 + 4 * lane, (live && !(st && sw == 7)) ? 2 : 0, tag, w);
                    float c[4];
#pragma unroll
                    for (int e = 0; e < 4; e++) {
                        c[e] = ll_val(w[0][e]) + ll_val(w[1][e]);
                        c[e] += __shfl_xor_sync(0xffffffffu, c[e], 4); c[e] += __shfl_xor_sync(0xffffffffu, c[e], 8); c[e] += __shfl_xor_sync(0xffffffffu, c[e], 16);
                    }
                    if (lane < 4) sts128(redO + st * 512 + sw * 64 + lane * 16, reinterpret_cast<const uint32_t*>(c));
                    bar256();
                    if (sw == 0) {
                        uint32_t u[4], v[4];
                        lds128(u, redO + st * 512 + (lane >> 2) * 64 + t * 16);
                        lds128(v, sb + SM_XO + t * 16);
                        const uint32_t b01 = lds32(sb + SM_BIAS + t * 8), b23 = lds32(sb + SM_BIAS + t * 8 + 4);
                        float x[4];
#pragma unroll
                        for (int e = 0; e < 4; e++) {
                            float y = __uint_as_float(u[e]);
                            y += __shfl_xor_sync(0xffffffffu, y, 4); y += __shfl_xor_sync(0xffffffffu, y, 8); y += __shfl_xor_sync(0xffffffffu, y, 16);
                            const float b2 = e == 0 ? bf_lo(b01) : (e == 1 ? bf_hi(b01) : (e == 2 ? bf_lo(b23) : bf_hi(b23)));
                            x[e] = bfr(__uint_as_float(v[e]) + (st == 0 ? bfr(y) : bfr(bfr(y) + b2)));
                        }
                        if (st == 0) {
                            if (lane < 4 * XR) st_w4(&g_xrow[2 + ob][(lane >> 2) % XR][16 * oo + 4 * t], (__float_as_uint(x[0]) | tag) & keep, (__float_as_uint(x[1]) | tag) & keep,
                                                     (__float_as_uint(x[2]) | tag) & keep, (__float_as_uint(x[3]) | tag) & keep);
                            __syncwarp();
                            if (live && lane < 4) sts128(sb + SM_XO + t * 16, reinterpret_cast<const uint32_t*>(x));
                            __syncwarp();
                        } else if (live && lane < 4) {
                            *reinterpret_cast<uint2*>(p.out + ob * DM + 16 * oo + 4 * lane) = make_uint2(pack_bf16(x[0], x[1]), pack_bf16(x[2], x[3]));
                        }
                    }
                };
                if (sw == 0) { sts32(redH + lane * 4, 0); sts32(redH + 128 + lane * 4, 0); }
                float o[2];
                if (live) {
                    mbar_wait_long(bars + (BAR_CTX + 3) * 8);
                    if (tid == 128 && mlp) {
                        mbar_expect_tx(wbar, 4 * 8192);
                        load_chunk<1, 0, false>(p, sb, wbar, pol); load_chunk<1, 1, false>(p, sb + 8192, wbar, pol);
                        load_chunk<1, 2, false>(p, sb + 16384, wbar, pol); load_chunk<1, 3, false>(p, sb + 24576, wbar, pol);
                    }
                }
                gather_o<2>(g_opart[2][cta & ~3], 32 * (cta & 3) + lane, tag0, live, o);
                if (live && sw == 0) TS(32 + 48 + 1);
                sts16(my + lane * 2, pack_bf16(o[0], 0.f)); sts16(my + 80 + lane * 2, pack_bf16(o[1], 0.f));
                __syncwarp();
                uint32_t bx[4];
                ldsm4(bx, vb);
                float acc[4][4];
#pragma unroll
                for (int u = 0; u < 4; u++) { acc[u][0] = acc[u][1] = acc[u][2] = acc[u][3] = 0.f; mma16816(acc[u], fo[u], bx[0], bx[1]); }
#pragma unroll
                for (int u = 0; u < 4; u++) mma16816(acc[u], fo[4 + u], bx[2], bx[3]);
                send4(acc, tagA);
                if (live && sw == 0) TS(32 + 48 + 2);
                if (owner) own(0, tagA); else bar256();
                if (live && sw == 0) TS(32 + 48 + 3);
                if (mlp) {
                    if (live) mbar_wait(wbar, 1);
#pragma unroll
                    for (int u = 0; u < 4; u++) {
                        ldsm4t(f1[u], sb + sw * 2048 + vrow * 32 + ((((lane >> 3) ^ (lane >> 2)) & 1) << 4) + u * 512);
                        ldsm4t(f2[u], ((sb + 16384 + sw * 2048 + aoff) ^ (u << 5)));
                    }
                    uint32_t w[1][4];
                    ll_gather<1, 0, 0>(g_xrow[2 + (lane >> 4)][cta % XR] + 64 * sw + 4 * (lane & 15), live, tagA, w);
                    if (live && sw == 0) TS(32 + 48 + 8);
                    sts64(my + 256 + (lane >> 4) * 144 + (lane & 15) * 8, __byte_perm(w[0][0], w[0][1], 0x7632), __byte_perm(w[0][2], w[0][3], 0x7632));
                    __syncwarp();
                    uint32_t b0[4], b1[4];
                    ldsm4(b0, xb); ldsm4(b1, xb + xs);
#pragma unroll
                    for (int u = 0; u < 4; u++) acc[u][0] = acc[u][1] = acc[u][2] = acc[u][3] = 0.f;
                    mma16816(acc[0], f1[0], b0[0], b0[1]); mma16816(acc[1], f1[1], b0[2], b0[3]);
                    mma16816(acc[2], f1[2], b1[0], b1[1]); mma16816(acc[3], f1[3], b1[2], b1[3]);
                    const float x0 = ll_val(w[0][0]), x1 = ll_val(w[0][1]), x2 = ll_val(w[0][2]), x3 = ll_val(w[0][3]);
                    float s1 = (x0 + x1) + (x2 + x3), s2 = (x0 * x0 + x1 * x1) + (x2 * x2 + x3 * x3);
#pragma unroll
                    for (int q = 8; q > 0; q >>= 1) { s1 += __shfl_xor_sync(0xffffffffu, s1, q); s2 += __shfl_xor_sync(0xffffffffu, s2, q); }
                    if (!(lane & 15)) { red_sf(redH + 192 + (lane >> 4) * 8, s1); red_sf(redH + 196 + (lane >> 4) * 8, s2); }
                    float h4[4];
#pragma unroll
                    for (int i = 0; i < 4; i++) h4[i] = (acc[0][i] + acc[1][i]) + (acc[2][i] + acc[3][i]);
                    const float ha = (t & 2) ? h4[2] : h4[0], hb = (t & 2) ? h4[3] : h4[1];
                    const int unit = g + 4 * (t & 2);
                    if (t & 1) red_sf(redH + 128 + unit * 4, ha);
                    else { red_sf(redH + unit * 8, ha); red_sf(redH + unit * 8 + 4, hb); }
                    bar256();
                    const float hv = ldsf(redH + unit * 8 + (t & 1) * 4), sw1 = ldsf(redH + 128 + unit * 4);
                    const float mean = ldsf(redH + 192 + (t & 1) * 8) * (1.f / DM);
                    const float rs = rsqrtf(fmaxf(ldsf(redH + 196 + (t & 1) * 8) * (1.f / DM) - mean * mean, 0.f) + 1e-5f);
                    sts16(my + (t & 1) * 80 + unit * 2, pack_bf16(gelu_tanh(bfr(bfr((hv - mean * sw1) * rs) + bias)), 0.f));
                    __syncwarp();
                    ldsm4(bx, vb);
#pragma unroll
                    for (int u = 0; u < 4; u++) { acc[u][0] = acc[u][1] = acc[u][2] = acc[u][3] = 0.f; mma16816(acc[u], f2[u], bx[0], bx[1]); }
                    if (live) send4(acc, tagB);
                    if (live && sw == 0) TS(32 + 48 + 5);
                }
                if (owner) own(1, tagB); else bar256();
                if (live && sw == 0) TS(32 + 48 + 6);
            }
            if (tid == 128) TSYNC(1);
            if (cta == NCTA - 1 && tid == 128) asm volatile("st.relaxed.gpu.global.u32 [%0], %1;" ::"l"(&g_epoch), "r"(epoch + 1) : "memory");
        }
    } else {
        asm volatile("setmaxnreg.dec.sync.aligned.u32 %0;" ::"n"(REG_LO));
        LaneC L;
        L.g = lane >> 2; L.t = lane & 3; L.v = (L.g >> 1) ^ L.t;
        L.src0 = 9 * L.t + 4 * (L.g & 1); L.src1 = 9 * L.t + 4 * ((L.g & 1) ^ 1);
        L.sx0 = (L.g & 1) ? 0x1044u : 0x4410u; L.sy0 = (L.g & 1) ? 0x3244u : 0x4432u;
        L.vrow = (lane & 7) + 8 * (lane >> 4);
        L.voff = ((lane >> 3) & 1) * 128 + ((lane & 7) << 4);

        if (warp < 3) {
            const int w = __shfl_sync(0xffffffffu, threadIdx.x >> 5, 0);
            const uint32_t koff = ((lane & 7) + 8 * ((lane >> 3) & 1)) * 256 + (((lane >> 4) ^ (lane & 7)) << 4);
            const uint32_t voff = HALF_B + L.vrow * 256 + L.voff;
            const int qrow = 4 * (L.g & 3) + L.t;
            const uint32_t qoff = sb + SM_Q + qrow * 64 + (((L.g >> 2) ^ ((qrow >> 1) & 3)) << 4);
            Ctx SA, SB;
            SA.o[0] = SA.o[1] = SA.o[2] = SA.o[3] = 0.f; SA.l = 0.f; SA.m = -INFINITY;
            SB = SA;
            uint32_t pa = sb + SM_TAB + w * LA * 8, pb = sb + SM_TAB + (3 * LA + w * LB) * 8;
            mbar_wait(bars + BAR_TAB * 8, 0);
            uint2 dA = uniform2(lds64(pa)), dB = uniform2(lds64(pb));
            uint32_t flushed = 0, idle = 0;
            auto run = [&](const uint2 d, Ctx& S, int ring) {
                const uint32_t tile = sb + ((d.x >> 16) & 15) * SLOT_B;
                const int ctx = (d.x >> 14) & 3;
                if (!(d.x & D_NOPROC)) process_tile(S, tile, qoff + (ctx & 1) * 1024, koff, voff, L, d.y, bars, p, pol);
                else if (((d.y & 7) - 1u) < 2u) issue_fill<true>(d.y, tile, bars, p, pol);
                if ((d.y & 7) == F_FREE) { __syncwarp(); if (lane == 0) mbar_arrive(bars + ((d.y >> 4) & 0x7ff)); }
                if (d.x & (D_FLUSH | D_PRE)) {
                    if (d.x & D_FLUSH) {
                        flush_ctx(S, sb + SM_PART + ((ctx & 1) * 3 + w) * 528, !((flushed >> ctx) & 1), lane, L);
                        flushed |= 1u << ctx;
                        TS(ring * 12 + ctx * 3 + w);
                    }
                    if (lane == 0) mbar_arrive(bars + (((d.x & D_FLUSH) ? BAR_CTX : BAR_PRE) + ctx) * 8);
                }
            };
            while (true) {
                if (!(dA.x & D_END) && mbar_test_warp(bars + (dA.x & 0x7ff), (dA.x >> 11) & 1)) {
                    pa += 8;
                    const uint2 nx = lds64(pa);
                    run(dA, SA, 0);
                    dA = uniform2(nx);
                    TS(128 + w * LB + ((pa - 8 - sb - SM_TAB) >> 3));
                } else if (!(dB.x & D_END) && mbar_test_warp(bars + (dB.x & 0x7ff), (dB.x >> 11) & 1)) {
                    pb += 8;
                    const uint2 nx = lds64(pb);
                    run(dB, SB, 1);
                    dB = uniform2(nx);
                    TS(128 + w * (LA + LB) + LA + ((pb - 8 - sb - SM_TAB - (3 * LA + w * LB) * 8) >> 3));
                } else {
                    if (dA.x & dB.x & D_END) break;
                    if (++idle > (1u << 25)) __trap();
                    continue;
                }
                idle = 0;
            }
        } else {
            TS(24);
            const int ob = cta >= 96 ? 0 : 1, oo = cta & 31;
            asm volatile("cp.async.wait_all;" ::: "memory");
            __syncwarp();
            const uint32_t epoch = lds32(sb + SM_EPOCH);
            if (lane < 16) stsf(sb + SM_XO + lane * 4, bf_lo(lds16(sb + SM_XN + ob * XS + (16 * oo + lane) * 2)));
            __syncwarp();
            const uint32_t tag0 = epoch % 15u + 1u, ubase = (epoch % 15u) * 6u;
            const uint32_t xnb = sb + SM_XN;
            auto fresh = [&]() { int l = lane; asm volatile("" : "+r"(l)); return l; };
            auto a128 = [&](int l, int k) -> uint32_t { return (((l & 7) + 8 * (l >> 4)) * 128 + ((((l >> 3) & 1) ^ (l & 7)) << 4)) ^ (k << 5); };
            auto a32 = [&](int l, int k) -> uint32_t { return ((l & 7) + 8 * (l >> 4)) * 32 + ((((l >> 3) ^ (l >> 2)) & 1) << 4) + k * 512; };
            auto a64 = [&](int l, int k) -> uint32_t { return ((l & 7) + 8 * (l >> 4)) * 64 + (((2 * (k & 1) + ((l >> 3) & 1)) ^ ((l >> 1) & 3)) << 4) + (k >> 1) * 1024; };
            auto vb_f = [&]() -> uint32_t { return sb + SM_V + (fresh() >> 3) * 16; };
            auto xb_f = [&]() -> uint32_t { const int l = fresh(); return xnb + (l & 1) * XS + (l >> 3) * 16; };
            auto reset_o = [&](int ctx) {
                int l = lane; asm volatile("" : "+r"(l));
                uint32_t* dst = g_opart[ctx][cta] + l;
#pragma unroll
                for (int i = 0; i < 4; i++) st_w(dst + 32 * i, 0);
                if (lane < 8) st_w(dst + 128, 0);
            };
            auto publish = [&](int ctx) {
                mbar_wait(bars + (BAR_CTX + ctx) * 8, 0);
                const uint32_t pa = sb + SM_PART + (ctx & 1) * 3 * 528;
                const float m0 = ldsf(pa + 512), m1 = ldsf(pa + 528 + 512), m2 = ldsf(pa + 1056 + 512);
                const float Mt = ll_val(__float_as_uint(fmaxf(m0, fmaxf(m1, m2))));
                const float f0 = ex2(m0 - Mt), f1 = ex2(m1 - Mt), f2 = ex2(m2 - Mt);
                int l = lane; asm volatile("" : "+r"(l));
                uint32_t* dst = g_opart[ctx][cta] + l;
#pragma unroll
                for (int i = 0; i < 4; i++) {
                    const uint32_t a = pa + (l + 32 * i) * 4;
                    ll_store(dst + 32 * i, ldsf(a) * f0 + ldsf(a + 528) * f1 + ldsf(a + 1056) * f2, tag0);
                }
                if (lane < 8) ll_store(dst + 128, lane ? ldsf(pa + 516) * f0 + ldsf(pa + 528 + 516) * f1 + ldsf(pa + 1056 + 516) * f2 : Mt, tag0);
            };
#pragma unroll 1
            for (int gi = 0; gi < 5; gi++) {
                const int h = cta >> 2, j = cta & 3, bb = (gi - 1) & 1;
                const bool owner = cta >= 64 && ob == bb;
                auto outbox_p = [&]() { const int l = fresh(); return &g_inbox[bb][l & 3][cta][l >> 2]; };
                auto qout_p = [&]() { const int l = fresh(); return g_qpart[gi ? 2 + bb : 0][cta] + 16 * (l & 1) + 8 * ((l >> 1) & 1) + (l >> 2); };
                auto xout_p = [&]() { const int l = fresh(); return &g_xrow[ob][(l >> 2) % XR][16 * oo + 4 * (l & 3)]; };
                if (gi != 3) {
                    if (gi) { mbar_wait_long(bars + (BAR_PRE + gi - 1) * 8); reset_o(gi - 1); }
                    if (gi < 3) {
                        uint32_t* const qout = qout_p();
                        uint32_t* const outbox = outbox_p();
                        st_w(qout, 0); st_w(qout + 32, 0); st_w(qout + 64, 0); st_w(qout + 96, 0);
                        if (gi) {
#pragma unroll
                            for (int i = 0; i < 8; i++) { st_w(outbox + i * 4 * NCTA * 16, 0); st_w(outbox + i * 4 * NCTA * 16 + 8, 0); }
                            if (owner && lane < 4 * XR) st_w4(xout_p(), 0, 0, 0, 0);
                        } else {
                            st_w(qout + NCTA * 128, 0); st_w(qout + NCTA * 128 + 32, 0); st_w(qout + NCTA * 128 + 64, 0); st_w(qout + NCTA * 128 + 96, 0);
                        }
                    }
                }
                if (gi >= 3) { publish(gi - 1); TS(32 + 48); continue; }
#pragma unroll 1
                for (int st = (gi == 0 ? 2 : 0); st < 3; st++) {
                    const uint32_t tag = (ubase + 2 * gi + st) % 15u + 1u, tagp = (ubase + 2 * gi + st + 14u) % 15u + 1u;
                    uint32_t f[2][8][4];
                    if (gi == 0) {
                        float x[2][16];
#pragma unroll
                        for (int i = 0; i < 8; i++) {
                            uint32_t v[2];
                            asm volatile("ld.shared.v2.u32 {%0,%1}, [%2];" : "=r"(v[0]), "=r"(v[1]) : "r"(xnb + (i >> 2) * XS + (128 * (i & 3) + 4 * lane) * 2) : "memory");
                            float* xx = &x[i >> 2][4 * (i & 3)];
                            xx[0] = bf_lo(v[0]); xx[1] = bf_hi(v[0]); xx[2] = bf_lo(v[1]); xx[3] = bf_hi(v[1]);
                        }
                        ln_store2(x, xnb, lane);
                    }
                    W.wait3();
                    {
                        const int l = fresh();
#pragma unroll
                        for (int k = 0; k < 4; k++) {
                            const uint32_t a = W.a[0] + (st == 0 ? a128(l, k) : (st == 1 ? a32(l, k) : a64(l, k)));
#pragma unroll
                            for (int u = 0; u < 4; u++) ldsm4t(f[u >> 1][4 * (u & 1) + k], a + u * 2048);
                        }
                    }
                    if (st == 0) load_fourth<0>(p, W, pol);
                    else if (st == 2) load_fourth<2>(p, W, pol);
                    else if (cta < NMLP) load_fourth<1>(p, W, pol);
                    if (st == 0) {
                        publish(bb);
                        TS(32 + gi * 16);
                        float o1[1];
                        gather_o<1>(g_opart[bb][4 * h], 32 * j + fresh(), tag0, true, o1);
                        sts16(sb + SM_V + lane * 2, pack_bf16(o1[0], 0.f));
                        __syncwarp();
                        uint32_t bx[4];
                        ldsm4(bx, vb_f());
                        TS(32 + gi * 16 + 1);
                        {
                            uint32_t* const outbox = outbox_p();
                            uint32_t* d = outbox;
                            const int l = fresh();
#pragma unroll 1
                            for (int c = 0; c < 4; c++) {
                                if (c == 2) W.wait4();
                                const uint32_t nx = (c == 0 ? W.a[1] : (c == 1 ? W.a[2] : W.a[0])) + a128(l, 0);
#pragma unroll
                                for (int hf = 0; hf < 2; hf++) {
                                    float acc[4][4], o[4];
#pragma unroll
                                    for (int u = 0; u < 4; u++) {
                                        acc[u][0] = acc[u][1] = acc[u][2] = acc[u][3] = 0.f;
                                        mma16816(acc[u], f[hf][u], bx[0], bx[1]);
                                    }
#pragma unroll
                                    for (int u = 0; u < 4; u++) mma16816(acc[u], f[hf][4 + u], bx[2], bx[3]);
                                    frag8(f[hf], nx + hf * 4096);
                                    pick4(o, acc[0], acc[1], acc[2], acc[3], l & 3);
                                    ll_store(d, o[0], tag); ll_store(d + 8, o[2], tag);
                                    d += 4 * NCTA * 16;
                                }
                            }
                        }
                        W.rotate();
                        TS(32 + gi * 16 + 2);
                        if (!owner) load_stage<1, false>(p, W, pol);
                    } else {
                        float s1 = 0.f, s2 = 0.f;
                        if (gi && (st == 2 || cta < NMLP)) {
                            uint32_t w[4][4];
                            ll_gather<4, 128, 0>(g_xrow[bb][cta % XR] + 4 * fresh(), 4, tagp, w);
                            TS(32 + gi * 16 + 7 + st);
                            float u[4], v[4];
#pragma unroll
                            for (int i = 0; i < 4; i++) {
                                sts64(xnb + (128 * i + 4 * lane) * 2, __byte_perm(w[i][0], w[i][1], 0x7632), __byte_perm(w[i][2], w[i][3], 0x7632));
                                const float x0 = ll_val(w[i][0]), x1 = ll_val(w[i][1]), x2 = ll_val(w[i][2]), x3 = ll_val(w[i][3]);
                                u[i] = (x0 + x1) + (x2 + x3);
                                v[i] = (x0 * x0 + x1 * x1) + (x2 * x2 + x3 * x3);
                            }
                            s1 = (u[0] + u[1]) + (u[2] + u[3]); s2 = (v[0] + v[1]) + (v[2] + v[3]);
                        }
                        __syncwarp();
                        auto row_stats = [&]() {
#pragma unroll
                            for (int o = 16; o > 0; o >>= 1) { s1 += __shfl_xor_sync(0xffffffffu, s1, o); s2 += __shfl_xor_sync(0xffffffffu, s2, o); }
                            s1 *= (1.f / DM);
                            s2 = rsqrtf(fmaxf(s2 * (1.f / DM) - s1 * s1, 0.f) + 1e-5f);
                        };
                        if (st == 2) {
                            TS(32 + gi * 16 + 10);
                            uint32_t bq[4][4];
                            {
                                const uint32_t xb = xb_f() + 256 * j;
#pragma unroll
                                for (int u = 0; u < 4; u++) ldsm4(bq[u], xb + 64 * u);
                            }
                            row_stats();
                            uint32_t* d = qout_p();
                            const int l = fresh();
#pragma unroll 1
                            for (int c = 0; c < 4; c++) {
                                if (c == 2) W.wait4();
                                const uint32_t nx = c == 0 ? W.a[1] : (c == 1 ? W.a[2] : W.a[0]);
                                float acc[4][4];
#pragma unroll
                                for (int k = 0; k < 4; k++) acc[k][0] = acc[k][1] = acc[k][2] = acc[k][3] = 0.f;
#pragma unroll
                                for (int u = 0; u < 4; u++) {
#pragma unroll
                                    for (int k = 0; k < 4; k++) mma16816(acc[k], f[u >> 1][4 * (u & 1) + k], bq[u][k & 2], bq[u][(k & 2) + 1]);
#pragma unroll
                                    for (int k = 0; k < 4; k++) ldsm4t(f[u >> 1][4 * (u & 1) + k], nx + a64(l, k) + u * 2048);
                                }
                                float r4[4];
#pragma unroll
                                for (int i = 0; i < 4; i++) r4[i] = (l & 1) ? acc[1][i] + acc[3][i] : acc[0][i] + acc[2][i];
                                const float va = (l & 2) ? r4[2] : r4[0], vb2 = (l & 2) ? r4[3] : r4[1];
                                if (gi) ll_store(d, (va - s1 * vb2) * s2, tag0);
                                else { ll_store(d, va, tag0); ll_store(d + NCTA * 128, vb2, tag0); }
                                d += 32;
                            }
                            W.rotate();
                            TS(32 + gi * 16 + 11);
                            break;
                        }
                        TS(32 + gi * 16 + 12);
                        if (cta < NMLP) {
                            float hh[4][4];
#pragma unroll
                            for (int u = 0; u < 4; u++) hh[u][0] = hh[u][1] = hh[u][2] = hh[u][3] = 0.f;
                            const uint32_t xb = xb_f();
                            const int l = fresh();
#pragma unroll 1
                            for (int c = 0; c < 2; c++) {
                                uint32_t na[4];
#pragma unroll
                                for (int k = 0; k < 4; k++) na[k] = c == 0 ? W.a[1] + a32(l, k) : W.a[2] + a128(l, k);
#pragma unroll
                                for (int s = 0; s < 4; s++) {
                                    uint32_t b0[4], b1[4];
                                    ldsm4(b0, xb + 512 * c + 128 * s); ldsm4(b1, xb + 512 * c + 128 * s + 64);
                                    mma16816(hh[0], f[s >> 1][4 * (s & 1)], b0[0], b0[1]); mma16816(hh[1], f[s >> 1][4 * (s & 1) + 1], b0[2], b0[3]);
                                    mma16816(hh[2], f[s >> 1][4 * (s & 1) + 2], b1[0], b1[1]); mma16816(hh[3], f[s >> 1][4 * (s & 1) + 3], b1[2], b1[3]);
#pragma unroll
                                    for (int k = 0; k < 4; k++) ldsm4t(f[s >> 1][4 * (s & 1) + k], na[k] + s * 2048);
                                }
                                if (c == 0) row_stats();
                            }
                            float hs4[4];
#pragma unroll
                            for (int i = 0; i < 4; i++) hs4[i] = (hh[0][i] + hh[1][i]) + (hh[2][i] + hh[3][i]);
                            const float hv = (((l & 2) ? hs4[2] : hs4[0]) - s1 * ((l & 2) ? hs4[3] : hs4[1])) * s2;
                            const float bias = bf_lo(lds16(sb + SM_BIAS + 32 + ((l >> 2) + 4 * (l & 2)) * 2));
                            uint32_t* const outbox = outbox_p();
                            sts16(sb + SM_V + ((l >> 2) + 4 * (l & 2)) * 2, pack_bf16(gelu_tanh(bfr(bfr(hv) + bias)), 0.f));
                            __syncwarp();
                            uint32_t bx[4];
                            ldsm4(bx, vb_f());
                            W.wait4();
                            uint32_t* d = outbox;
#pragma unroll 1
                            for (int c = 0; c < 2; c++) {
#pragma unroll
                                for (int s = 0; s < 4; s++) {
                                    float acc[4][4], o[4];
#pragma unroll
                                    for (int u = 0; u < 4; u++) {
                                        acc[u][0] = acc[u][1] = acc[u][2] = acc[u][3] = 0.f;
                                        mma16816(acc[u], f[s >> 1][4 * (s & 1) + u], bx[0], bx[1]);
                                    }
#pragma unroll
                                    for (int u = 0; u < 4; u++) ldsm4t(f[s >> 1][4 * (s & 1) + u], W.a[0] + a128(l, u) + s * 2048);
                                    pick4(o, acc[0], acc[1], acc[2], acc[3], l & 3);
                                    ll_store(d, o[0], tag); ll_store(d + 8, o[2], tag);
                                    d += 4 * NCTA * 16;
                                }
                            }
                        }
                        W.rotate();
                        TS(32 + gi * 16 + 5);
                        if (!owner) load_stage<2, false>(p, W, pol);
                    }
                    if (owner) {
                        uint32_t w[16][4];
                        ll_gather<16, 128, 0>(&g_inbox[ob][oo][0][0] + 4 * fresh(), st == 0 ? 16 : NMLP / 8, tag, w);
                        float xown[4];
                        lds128(reinterpret_cast<uint32_t*>(xown), sb + SM_XO + (lane & 3) * 16);
                        const uint32_t b01 = lds32(sb + SM_BIAS + (lane & 3) * 8), b23 = lds32(sb + SM_BIAS + (lane & 3) * 8 + 4);
                        const float b2own[4] = {bf_lo(b01), bf_hi(b01), bf_lo(b23), bf_hi(b23)};
#pragma unroll
                        for (int e = 0; e < 4; e++) {
                            float c[4];
#pragma unroll
                            for (int i = 0; i < 4; i++) c[i] = (ll_val(w[i][e]) + ll_val(w[4 + i][e])) + (ll_val(w[8 + i][e]) + ll_val(w[12 + i][e]));
                            float t = (c[0] + c[1]) + (c[2] + c[3]);
                            t += __shfl_xor_sync(0xffffffffu, t, 4); t += __shfl_xor_sync(0xffffffffu, t, 8); t += __shfl_xor_sync(0xffffffffu, t, 16);
                            xown[e] = bfr(xown[e] + (st == 0 ? bfr(t) : bfr(bfr(t) + b2own[e])));
                        }
                        if (lane < 4 * XR) st_w4(xout_p(), __float_as_uint(xown[0]) | tag, __float_as_uint(xown[1]) | tag, __float_as_uint(xown[2]) | tag, __float_as_uint(xown[3]) | tag);
                        __syncwarp();
                        if (lane < 4) sts128(sb + SM_XO + lane * 16, reinterpret_cast<const uint32_t*>(xown));
                        TS(32 + gi * 16 + 3 + 3 * st);
                        if (st == 0) load_stage<1, false>(p, W, pol); else load_stage<2, false>(p, W, pol);
                    }
                }
                {
                    uint32_t w[8][4];
                    ll_gather<8, 128, NCTA * 128>(g_qpart[gi ? 2 + bb : 0][4 * h] + 4 * fresh(), gi ? 4 : 8, tag0, w);
#pragma unroll
                    for (int bi = 0; bi < 2; bi++) {
                        if (bi == 0 || gi == 0) {
                            float q[4];
#pragma unroll
                            for (int e = 0; e < 4; e++) q[e] = (ll_val(w[4 * bi][e]) + ll_val(w[4 * bi + 1][e])) + (ll_val(w[4 * bi + 2][e]) + ll_val(w[4 * bi + 3][e]));
                            const uint32_t w0 = pack_bf16(q[0], q[1]), w1 = pack_bf16(q[2], q[3]);
                            const int ch = lane >> 1;
#pragma unroll
                            for (int kp = 0; kp < 4; kp++) {
                                const int jj = ch ^ kp;
#pragma unroll
                                for (int e = 0; e < 2; e++) {
                                    const int row = 4 * kp + 2 * (lane & 1) + e;
                                    sts32(sb + SM_Q + (gi ? bb : bi) * 1024 + row * 64 + (((jj >> 2) ^ ((row >> 1) & 3)) << 4) + (jj & 3) * 4, e ? w1 : w0);
                                }
                            }
                        }
                    }
                    __syncwarp();
                    if (lane < (gi ? 1 : 2)) mbar_arrive(bars + (BAR_Q + (gi ? 2 + bb : lane)) * 8);
                }
                TS(32 + gi * 16 + 7);
                load_stage<0, false>(p, W, pol);
                if (gi == 0) fill_ones(xnb + XS, lane);
            }
        }
    }
}

typedef CUresult (*EncodeFn)(CUtensorMap*, CUtensorMapDataType, cuuint32_t, void*, const cuuint64_t*, const cuuint64_t*, const cuuint32_t*,
                             const cuuint32_t*, CUtensorMapInterleave, CUtensorMapSwizzle, CUtensorMapL2promotion, CUtensorMapFloatOOBfill);
void encode2d(EncodeFn fn, CUtensorMap* m, void* base, uint64_t cols, uint64_t rows, uint32_t bcols, uint32_t brows, CUtensorMapSwizzle sw) {
    const cuuint64_t dim[2] = {cols, rows}, stride[1] = {cols * 2};
    const cuuint32_t box[2] = {bcols, brows}, es[2] = {1, 1};
    fn(m, CU_TENSOR_MAP_DATA_TYPE_BFLOAT16, 2, base, dim, stride, box, es, CU_TENSOR_MAP_INTERLEAVE_NONE, sw,
       CU_TENSOR_MAP_L2_PROMOTION_L2_128B, CU_TENSOR_MAP_FLOAT_OOB_FILL_NONE);
}

}

extern "C" void kernel_launch(void* const* d_in, const int* in_sizes, int n_in, void* d_out, int out_size) {
    (void)in_sizes; (void)n_in; (void)out_size;
    static EncodeFn enc = nullptr;
    if (!enc) {
        cudaFuncSetAttribute(fused_kernel, cudaFuncAttributeMaxDynamicSharedMemorySize, (int)SM_TOTAL);
        void* fn = nullptr;
        cudaDriverEntryPointQueryResult qr;
        cudaGetDriverEntryPoint("cuTensorMapEncodeTiled", &fn, cudaEnableDefault, &qr);
        enc = (EncodeFn)fn;
    }
    Params p;
    encode2d(enc, &p.mwq, d_in[3], HD, DM, 32, 128, CU_TENSOR_MAP_SWIZZLE_64B);
    encode2d(enc, &p.mwo, d_in[4], DM, HD, 64, 32, CU_TENSOR_MAP_SWIZZLE_128B);
    encode2d(enc, &p.mw1, d_in[6], FF, DM, 16, 256, CU_TENSOR_MAP_SWIZZLE_32B);
    encode2d(enc, &p.mw2, d_in[8], DM, FF, 64, 16, CU_TENSOR_MAP_SWIZZLE_128B);
    p.x = (const __nv_bfloat16*)d_in[0];
    p.k = (const __nv_bfloat16*)d_in[1];
    p.v = (const __nv_bfloat16*)d_in[2];
    p.b1 = (const __nv_bfloat16*)d_in[7];
    p.b2 = (const __nv_bfloat16*)d_in[9];
    p.out = (__nv_bfloat16*)d_out;
    p.zero = 0;
    fused_kernel<<<NCTA, 384, SM_TOTAL>>>(p);
}
```

```cpp
#include <cuda_runtime.h>
#include <cuda.h>
#include <cuda_bf16.h>
#include <stdint.h>

namespace {

constexpr int NCTA = 128;
constexpr int DM = 512, FF = 1792, HD = 4096;
constexpr int NMLP = 112;
constexpr uint32_t HALF_B = 8192;
constexpr uint32_t SLOT_B = 16384;
constexpr int NT = 64;

constexpr int REG_LO = 104, REG_HI = 200;
constexpr int PRE = 2;
constexpr int MIX = 1;
constexpr int NSB = 3;
constexpr int NB = 3 * NSB, NSLOT = 3 + NB;
constexpr int NRF = 12;
constexpr int NL2 = 20;
constexpr int NNR = NT - NB - NRF - NL2;
constexpr int TB = NT - NB;
constexpr int NZ = NRF + NL2;

constexpr int BAR_FULL = 0;
constexpr int BAR_RF = NSLOT, BAR_CAP = BAR_RF + 2 * NRF, BAR_FREE = BAR_CAP + 2 * NRF, BAR_DUMP = BAR_FREE + 2 * NRF;
constexpr int BAR_Q = BAR_DUMP + 2 * NRF, BAR_CTX = BAR_Q + 4, BAR_TAB = BAR_CTX + 4, BAR_W = BAR_TAB + 1, BAR_PRE = BAR_W + 2, NBAR = BAR_PRE + 4;

enum { F_NONE = 0, F_TILE = 1, F_KEEP = 2, F_FREE = 4, F_NORM = 8 };
constexpr uint32_t D_NOPROC = 1u << 12, D_FLUSH = 1u << 13, D_PRE = 1u << 21, D_END = 1u << 31;
struct Desc { uint32_t w0, w1; };
constexpr int LA = 66, LB = 42;
struct Tables {
    Desc a[3][LA];
    Desc b[3][LB];
    uint32_t inita[4];
    int capslot[2][NRF], dumpslot[2][NRF];
    bool ok;
};
enum { K_TILE = 0, K_CAP = 1, K_L2 = 2, K_DUMP = 4, K_RES = 5 };
struct Item { int kind, ctx, idx; };
constexpr uint32_t mk0(int bar, int par, int ctx, int slot) { return (uint32_t)(bar * 8) | ((uint32_t)par << 11) | ((uint32_t)ctx << 14) | ((uint32_t)slot << 16); }
constexpr uint32_t mkfill(const Item& x, int slot) {
    const int b = x.ctx & 1;
    if (x.kind == K_DUMP) return F_FREE | ((uint32_t)((BAR_FREE + b * NRF + x.idx - NNR) * 8) << 4);
    if (x.kind == K_RES) return F_NONE;
    const int bar = x.kind == K_CAP ? BAR_RF + b * NRF + x.idx - NNR : BAR_FULL + slot;
    const uint32_t norm = x.ctx == 0 && (x.idx < NNR || x.idx >= TB) ? F_NORM : 0;
    return (x.kind == K_L2 ? F_KEEP : F_TILE) | norm | ((uint32_t)(bar * 8) << 4) | ((uint32_t)(b * 8192 + x.idx) << 16);
}
constexpr Tables build_tables() {
    Tables T{};
    T.ok = true;
    Item A[256] = {};
    int n = 0;
    auto tiles = [&](int kind, int ctx, int lo, int hi) { for (int i = lo; i < hi; i++) A[n++] = Item{kind, ctx, i}; };
    for (int c = 0; c < 2; c++) { tiles(K_TILE, c, 0, NNR); tiles(K_CAP, c, NNR, NNR + NRF); tiles(K_L2, c, NNR + NRF, TB); }
    tiles(K_TILE, 2, 0, NNR);
    tiles(K_TILE, 3, 0, NNR);
    const int NA = n;
    for (int w = 0; w < 3; w++) {
        int m = 0, par = 0, cur = -1;
        T.inita[w] = mkfill(A[w], w);
        for (int i = w; i < NA; i += 3) {
            const Item x = A[i];
            const uint32_t fill = i + 3 < NA ? mkfill(A[i + 3], w) : (uint32_t)F_NONE;
            if (x.ctx != cur) T.a[w][m++] = Desc{mk0(BAR_Q + x.ctx, 0, 0, w) | D_NOPROC, F_NONE};
            cur = x.ctx;
            int left = 0;
            for (int k = i + 3; k < NA; k += 3) if (A[k].ctx == cur) left++;
            const uint32_t fl = (left == 0 ? D_FLUSH : 0u) | (cur != 2 && w == 0 && left == PRE ? D_PRE : 0u);
            const int b = x.ctx & 1;
            if (x.kind == K_CAP) {
                T.capslot[b][x.idx - NNR] = w;
                T.a[w][m++] = Desc{mk0(BAR_RF + b * NRF + x.idx - NNR, 0, x.ctx, w) | fl, F_NONE};
                T.a[w][m++] = Desc{mk0(BAR_CAP + b * NRF + x.idx - NNR, 0, 0, w) | D_NOPROC, fill};
            } else {
                T.a[w][m++] = Desc{mk0(BAR_FULL + w, par, x.ctx, w) | fl, fill};
                par ^= 1;
            }
        }
        T.a[w][m++] = Desc{D_END, F_NONE};
        if (m > LA) T.ok = false;
        const int s0 = 3 + NSB * w;
        Item B[64] = {};
        int nb = 0;
        for (int h = 0; h < 2; h++) {
            for (int k = 0; k < NSB; k++) B[nb++] = Item{K_TILE, h, TB + s0 - 3 + k};
            for (int k = 0; k < NSB; k++) B[nb++] = Item{K_RES, 2 + h, 0};
            int zd = w, zl = NRF + (w + 3 - NRF % 3) % 3;
            while (zd < NRF || zl < NZ) {
                if (zd < NRF) { B[nb++] = Item{K_DUMP, 2 + h, NNR + zd}; zd += 3; }
                for (int k = 0; (k < MIX || zd >= NRF) && zl < NZ; k++) { B[nb++] = Item{K_TILE, 2 + h, NNR + zl}; zl += 3; }
            }
        }
        m = 0;
        int parb[NSB] = {};
        for (int k = 0; k < NSB; k++) T.b[w][m++] = Desc{mk0(BAR_FULL + (k ? s0 + k - 1 : w), 0, 0, s0 + k) | D_NOPROC, mkfill(B[k], s0 + k)};
        cur = -1;
        for (int i = 0; i < nb; i++) {
            const Item x = B[i];
            const int k = i % NSB, slot = s0 + k;
            const uint32_t fill = i + NSB < nb ? mkfill(B[i + NSB], slot) : (uint32_t)F_NONE;
            if (x.ctx != cur && x.kind != K_RES) T.b[w][m++] = Desc{mk0(BAR_Q + x.ctx, 0, 0, slot) | D_NOPROC, F_NONE};
            cur = x.ctx;
            const uint32_t fl = (i + 1 == nb || B[i + 1].ctx != cur) ? D_FLUSH : 0u;
            const int b = x.ctx & 1;
            if (x.kind == K_RES) T.b[w][m++] = Desc{mk0(BAR_Q + x.ctx, 0, x.ctx, slot) | fl, fill};
            else if (x.kind == K_DUMP) {
                T.dumpslot[b][x.idx - NNR] = slot;
                T.b[w][m++] = Desc{mk0(BAR_DUMP + b * NRF + x.idx - NNR, 0, x.ctx, slot) | fl, fill};
            } else { T.b[w][m++] = Desc{mk0(BAR_FULL + slot, parb[k], x.ctx, slot) | fl, fill}; parb[k] ^= 1; }
        }
        T.b[w][m++] = Desc{D_END, F_NONE};
        if (m > LB) T.ok = false;
    }
    return T;
}
constexpr Tables HT = build_tables();
static_assert(HT.ok, "schedule does not fit");
constexpr unsigned long long pack_slots(const int* v) { unsigned long long r = 0; for (int i = 0; i < NRF; i++) r |= (unsigned long long)v[i] << (4 * i); return r; }
constexpr unsigned long long CAP0 = pack_slots(HT.capslot[0]), CAP1 = pack_slots(HT.capslot[1]);
constexpr unsigned long long DUMP0 = pack_slots(HT.dumpslot[0]), DUMP1 = pack_slots(HT.dumpslot[1]);
constexpr uint32_t INITA0 = HT.inita[0], INITA1 = HT.inita[1], INITA2 = HT.inita[2];
static_assert(NRF <= 16, "slot packing");
__device__ const Tables g_tab = build_tables();
constexpr uint32_t TAB_BYTES = (3 * LA + 3 * LB) * 8;
static_assert(TAB_BYTES % 16 == 0, "bulk copy size");

constexpr uint32_t SM_W = NSLOT * SLOT_B;
constexpr uint32_t SM_Q = SM_W + 3 * 8192;
constexpr uint32_t SM_PART = SM_Q + 2048;
constexpr uint32_t XS = 1040;
constexpr uint32_t SM_XN = SM_PART + 6 * 528;
constexpr uint32_t SM_BIAS = SM_XN + 2 * XS;
constexpr uint32_t SM_V = SM_BIAS + 64;
constexpr uint32_t SM_XO = SM_V + 80;
constexpr uint32_t SM_EPOCH = SM_XO + 64;
constexpr uint32_t SM_TAB = SM_XO + 80;
constexpr uint32_t SM_BAR = SM_TAB + TAB_BYTES;
constexpr uint32_t SM_TOTAL = SM_BAR + NBAR * 8;
static_assert(SM_TOTAL <= 232448 && NBAR * 8 < 2048, "shared memory budget");

constexpr int XR = 16;
__device__ __align__(128) uint32_t g_opart[4][NCTA][160];
__device__ __align__(128) uint32_t g_qpart[4][NCTA][128];
__device__ __align__(128) uint32_t g_inbox[2][32][NCTA][16];
__device__ __align__(128) uint32_t g_xrow[4][16][1024];
__device__ unsigned g_epoch;
#define TS(i) do {} while (0)
#define TSYNC(k) do {} while (0)

struct Params {
    const __nv_bfloat16 *x, *k, *v, *b1, *b2, *wq;
    __nv_bfloat16* out;
    uint32_t zero;
    CUtensorMap mwq, mwo, mw1, mw2;
};

__device__ __forceinline__ void mbar_init(uint32_t bar, int cnt) { asm volatile("mbarrier.init.shared::cta.b64 [%0], %1;" ::"r"(bar), "r"(cnt)); }
__device__ __forceinline__ void mbar_expect_tx(uint32_t bar, uint32_t bytes) { asm volatile("mbarrier.arrive.expect_tx.shared::cta.b64 _, [%0], %1;" ::"r"(bar), "r"(bytes) : "memory"); }
__device__ __forceinline__ void mbar_arrive(uint32_t bar) { asm volatile("mbarrier.arrive.shared::cta.b64 _, [%0];" ::"r"(bar) : "memory"); }
__device__ __forceinline__ void mbar_arrive_elect(uint32_t bar) {
    asm volatile("{\n.reg .pred e;\nelect.sync _|e, 0xffffffff;\n@e mbarrier.arrive.shared::cta.b64 _, [%0];\n}" ::"r"(bar) : "memory");
}
__device__ __forceinline__ bool mbar_test(uint32_t bar, uint32_t parity) {
    uint32_t ok;
    asm volatile("{\n.reg .pred p;\nmbarrier.test_wait.parity.shared::cta.b64 p, [%1], %2;\nselp.u32 %0, 1, 0, p;\n}" : "=r"(ok) : "r"(bar), "r"(parity) : "memory");
    return ok;
}
__device__ __forceinline__ bool mbar_try(uint32_t bar, uint32_t parity) {
    uint32_t ok;
    asm volatile("{\n.reg .pred p;\nmbarrier.try_wait.parity.shared::cta.b64 p, [%1], %2;\nselp.u32 %0, 1, 0, p;\n}" : "=r"(ok) : "r"(bar), "r"(parity) : "memory");
    return ok;
}
__device__ __forceinline__ void mbar_wait(uint32_t bar, uint32_t parity) {
    uint32_t it = 0;
    while (!__all_sync(0xffffffffu, mbar_try(bar, parity))) { if (++it > (1u << 24)) __trap(); }
}
__device__ __forceinline__ void mbar_wait_long(uint32_t bar) {
    uint32_t it = 0, ok;
    do {
        asm volatile("{\n.reg .pred p;\nmbarrier.try_wait.parity.shared::cta.b64 p, [%1], 0, %2;\nselp.u32 %0, 1, 0, p;\n}" : "=r"(ok) : "r"(bar), "r"(2000u) : "memory");
        if (++it > (1u << 22)) __trap();
    } while (!__all_sync(0xffffffffu, ok));
}
__device__ __forceinline__ bool elect_one() {
    uint32_t r;
    asm volatile("{\n.reg .pred P;\nelect.sync _|P, 0xffffffff;\nselp.b32 %0, 1, 0, P;\n}" : "=r"(r));
    return r;
}
__device__ __forceinline__ bool mbar_test_warp(uint32_t bar, uint32_t parity) { return __all_sync(0xffffffffu, mbar_test(bar, parity)); }
__device__ __forceinline__ void bulk_g2s(uint32_t dst, const void* src, uint32_t bytes, uint32_t bar, uint64_t pol) {
    asm volatile("cp.async.bulk.shared::cluster.global.mbarrier::complete_tx::bytes.L2::cache_hint [%0], [%1], %2, [%3], %4;"
                 ::"r"(dst), "l"(src), "r"(bytes), "r"(bar), "l"(pol) : "memory");
}
__device__ __forceinline__ void half_fill(bool cond, bool arm, bool keep, uint32_t dst, const void* src, uint32_t bar, uint64_t pol, uint32_t zero) {
    asm volatile("{\n.reg .pred e, a, k;\n.reg .b32 t;\nelect.sync _|e, 0xffffffff;\nsetp.ne.and.u32 e, %0, 0, e;\nsetp.ne.and.u32 a, %1, 0, e;\n"
                 "@a mbarrier.arrive.expect_tx.shared::cta.b64 _, [%5], 16384;\n"
                 "@e cp.async.bulk.shared::cluster.global.mbarrier::complete_tx::bytes.L2::cache_hint [%3], [%4], 8192, [%5], %6;\n"
                 "ld.volatile.shared.u32 t, [%3];\nand.b32 t, t, %7;\nor.b32 t, t, %2;\nsetp.ne.and.u32 k, t, 0, e;\n"
                 "@k cp.async.bulk.prefetch.L2.global [%4], 8192;\n}"
                 ::"r"((uint32_t)cond), "r"((uint32_t)arm), "r"((uint32_t)keep), "r"(dst), "l"(src), "r"(bar), "l"(pol), "r"(zero) : "memory");
}
__device__ __forceinline__ void ldsm4(uint32_t (&r)[4], uint32_t a) {
    asm volatile("ldmatrix.sync.aligned.m8n8.x4.shared.b16 {%0,%1,%2,%3}, [%4];" : "=r"(r[0]), "=r"(r[1]), "=r"(r[2]), "=r"(r[3]) : "r"(a));
}
__device__ __forceinline__ void ldsm4t(uint32_t (&r)[4], uint32_t a) {
    asm volatile("ldmatrix.sync.aligned.m8n8.x4.trans.shared.b16 {%0,%1,%2,%3}, [%4];" : "=r"(r[0]), "=r"(r[1]), "=r"(r[2]), "=r"(r[3]) : "r"(a));
}
__device__ __forceinline__ void mma16816(float (&c)[4], const uint32_t (&a)[4], uint32_t b0, uint32_t b1) {
    asm volatile("mma.sync.aligned.m16n8k16.row.col.f32.bf16.bf16.f32 {%0,%1,%2,%3}, {%4,%5,%6,%7}, {%8,%9}, {%0,%1,%2,%3};"
                 : "+f"(c[0]), "+f"(c[1]), "+f"(c[2]), "+f"(c[3]) : "r"(a[0]), "r"(a[1]), "r"(a[2]), "r"(a[3]), "r"(b0), "r"(b1));
}
__device__ __forceinline__ void lds128(uint32_t* r, uint32_t a) {
    asm volatile("ld.shared.v4.u32 {%0,%1,%2,%3}, [%4];" : "=r"(r[0]), "=r"(r[1]), "=r"(r[2]), "=r"(r[3]) : "r"(a) : "memory");
}
__device__ __forceinline__ void sts128(uint32_t a, const uint32_t* r) {
    asm volatile("st.shared.v4.u32 [%0], {%1,%2,%3,%4};" ::"r"(a), "r"(r[0]), "r"(r[1]), "r"(r[2]), "r"(r[3]) : "memory");
}
__device__ __forceinline__ uint32_t lds32(uint32_t a) { uint32_t r; asm volatile("ld.shared.u32 %0, [%1];" : "=r"(r) : "r"(a) : "memory"); return r; }
__device__ __forceinline__ uint32_t lds16(uint32_t a) { uint16_t r; asm volatile("ld.shared.u16 %0, [%1];" : "=h"(r) : "r"(a) : "memory"); return r; }
__device__ __forceinline__ float ldsf(uint32_t a) { float r; asm volatile("ld.shared.f32 %0, [%1];" : "=f"(r) : "r"(a) : "memory"); return r; }
__device__ __forceinline__ void sts32(uint32_t a, uint32_t v) { asm volatile("st.shared.u32 [%0], %1;" ::"r"(a), "r"(v) : "memory"); }
__device__ __forceinline__ void sts16(uint32_t a, uint32_t v) { asm volatile("st.shared.u16 [%0], %1;" ::"r"(a), "h"((uint16_t)v) : "memory"); }
__device__ __forceinline__ void stsf(uint32_t a, float v) { asm volatile("st.shared.f32 [%0], %1;" ::"r"(a), "f"(v) : "memory"); }
__device__ __forceinline__ void sts64(uint32_t a, uint32_t v0, uint32_t v1) { asm volatile("st.shared.v2.u32 [%0], {%1,%2};" ::"r"(a), "r"(v0), "r"(v1) : "memory"); }
__device__ __forceinline__ void cp16(uint32_t dst, const void* src) { asm volatile("cp.async.cg.shared.global [%0], [%1], 16;" ::"r"(dst), "l"(src) : "memory"); }
__device__ __forceinline__ float ex2(float x) { float r; asm("ex2.approx.ftz.f32 %0, %1;" : "=f"(r) : "f"(x)); return r; }
__device__ __forceinline__ uint32_t pack_bf16(float lo, float hi) { uint32_t r; asm("cvt.rn.bf16x2.f32 %0, %1, %2;" : "=r"(r) : "f"(hi), "f"(lo)); return r; }
__device__ __forceinline__ float bf_lo(uint32_t v) { return __uint_as_float(v << 16); }
__device__ __forceinline__ float bf_hi(uint32_t v) { return __uint_as_float(v & 0xffff0000u); }
__device__ __forceinline__ float bfr(float x) { return __bfloat162float(__float2bfloat16_rn(x)); }
__device__ __forceinline__ uint32_t ll_pack(float v, uint32_t tag) { return (__float_as_uint(v) & ~15u) | tag; }
__device__ __forceinline__ float ll_val(uint32_t w) { return __uint_as_float(w & ~15u); }
__device__ __forceinline__ void st_w(uint32_t* p, uint32_t w) { asm volatile("st.relaxed.gpu.global.u32 [%0], %1;" ::"l"(p), "r"(w) : "memory"); }
__device__ __forceinline__ void st_w4(uint32_t* p, uint32_t a, uint32_t b, uint32_t c, uint32_t d) {
    asm volatile("st.relaxed.gpu.global.v4.u32 [%0], {%1,%2,%3,%4};" ::"l"(p), "r"(a), "r"(b), "r"(c), "r"(d) : "memory");
}
__device__ __forceinline__ void ll_store(uint32_t* p, float v, uint32_t tag) { st_w(p, ll_pack(v, tag)); }
__device__ __forceinline__ void ld_w4(const uint32_t* p, bool pred, uint32_t (&w)[4]) {
    asm volatile("{\n.reg .pred q;\nsetp.ne.u32 q, %5, 0;\n@q ld.relaxed.gpu.global.L1::no_allocate.v4.u32 {%0,%1,%2,%3}, [%4];\n}"
                 : "+r"(w[0]), "+r"(w[1]), "+r"(w[2]), "+r"(w[3]) : "l"(p), "r"((uint32_t)pred) : "memory");
}
__device__ __forceinline__ void ld_w2(const uint32_t* p, bool pred, uint32_t& a, uint32_t& b) {
    asm volatile("{\n.reg .pred q;\nsetp.ne.u32 q, %3, 0;\n@q ld.relaxed.gpu.global.L1::no_allocate.v2.u32 {%0,%1}, [%2];\n}" : "+r"(a), "+r"(b) : "l"(p), "r"((uint32_t)pred) : "memory");
}
__device__ __forceinline__ void ld_w1(const uint32_t* p, bool pred, uint32_t& a) {
    asm volatile("{\n.reg .pred q;\nsetp.ne.u32 q, %2, 0;\n@q ld.relaxed.gpu.global.L1::no_allocate.u32 %0, [%1];\n}" : "+r"(a) : "l"(p), "r"((uint32_t)pred) : "memory");
}
__device__ __forceinline__ bool miss4(const uint32_t (&w)[4], uint32_t tag) { return (((w[0] ^ tag) | (w[1] ^ tag) | (w[2] ^ tag) | (w[3] ^ tag)) & 15u) != 0; }
#define SPIN_GUARD(it) do { if (++(it) > (1u << 22)) __trap(); } while (0)

struct PVB { uint32_t x0, x1, y0, y1; };
struct LaneC {
    int g, t, v;
    int src0, src1;
    uint32_t sx0, sy0;
    uint32_t voff;
    int vrow;
};
__device__ __forceinline__ PVB spread(uint32_t pk, const LaneC& L) {
    uint32_t v0 = __shfl_sync(0xffffffffu, pk, L.src0), v1 = __shfl_sync(0xffffffffu, pk, L.src1);
    PVB b;
    b.x0 = __byte_perm(v0, 0, L.sx0); b.y0 = __byte_perm(v0, 0, L.sy0);
    b.x1 = __byte_perm(v1, 0, L.sx0 ^ 0x5454u); b.y1 = __byte_perm(v1, 0, L.sy0 ^ 0x7676u);
    return b;
}
__device__ __forceinline__ void pv_load(uint32_t (&a)[8][4], uint32_t base) {
#pragma unroll
    for (int c = 0; c < 8; c++) ldsm4t(a[c], base ^ (c << 4));
}
template <int U> __device__ __forceinline__ void raw_load(uint32_t (&r)[16], uint32_t a) {
    asm volatile("ld.shared.v4.u32 {%0,%1,%2,%3}, [%16];\nld.shared.v4.u32 {%4,%5,%6,%7}, [%16+512];\n"
                 "ld.shared.v4.u32 {%8,%9,%10,%11}, [%16+1024];\nld.shared.v4.u32 {%12,%13,%14,%15}, [%16+1536];\nmembar.cta; // %17"
                 : "=r"(r[0]), "=r"(r[1]), "=r"(r[2]), "=r"(r[3]), "=r"(r[4]), "=r"(r[5]), "=r"(r[6]), "=r"(r[7]), "=r"(r[8]), "=r"(r[9]),
                   "=r"(r[10]), "=r"(r[11]), "=r"(r[12]), "=r"(r[13]), "=r"(r[14]), "=r"(r[15]) : "r"(a), "n"(U) : "memory");
}
template <int U> __device__ __forceinline__ void raw_store(const uint32_t (&r)[16], uint32_t a) {
    asm volatile("st.shared.v4.u32 [%16], {%0,%1,%2,%3};\nst.shared.v4.u32 [%16+512], {%4,%5,%6,%7};\n"
                 "st.shared.v4.u32 [%16+1024], {%8,%9,%10,%11};\nst.shared.v4.u32 [%16+1536], {%12,%13,%14,%15};\nfence.proxy.async.shared::cta; // %17"
                 :: "r"(r[0]), "r"(r[1]), "r"(r[2]), "r"(r[3]), "r"(r[4]), "r"(r[5]), "r"(r[6]), "r"(r[7]), "r"(r[8]), "r"(r[9]),
                    "r"(r[10]), "r"(r[11]), "r"(r[12]), "r"(r[13]), "r"(r[14]), "r"(r[15]), "r"(a), "n"(U) : "memory");
}
template <int LO, int HI, bool LOAD> __device__ __forceinline__ void raw_dispatch(uint32_t (&r)[NRF][16], int u, uint32_t a) {
    if constexpr (HI - LO == 1) {
        if constexpr (LOAD) raw_load<LO>(r[LO], a); else raw_store<LO>(r[LO], a);
    } else {
        constexpr int MID = (LO + HI) / 2;
        if (u < MID) raw_dispatch<LO, MID, LOAD>(r, u, a); else raw_dispatch<MID, HI, LOAD>(r, u, a);
    }
}

struct Ctx { float o[4]; float m, l; };
constexpr float SCL = 0.08838834764831845f * 1.4426950408889634f;

__device__ __forceinline__ void process_tile(Ctx& S, uint32_t tile, uint32_t qaddr, uint32_t koff, uint32_t voff, const LaneC& L,
                                             uint32_t fill, uint32_t bars, const Params& p, uint64_t pol) {
    float sa0[4] = {0.f, 0.f, 0.f, 0.f}, sa1[4] = {0.f, 0.f, 0.f, 0.f}, sb0[4] = {0.f, 0.f, 0.f, 0.f}, sb1[4] = {0.f, 0.f, 0.f, 0.f};
    const uint32_t kb = tile + koff;
    {
        uint32_t q[4][4], a[4][4][4];
#pragma unroll
        for (int i = 0; i < 4; i++) {
            lds128(q[i], qaddr ^ (i << 4));
            const uint32_t k0 = kb ^ ((2 * i) << 5), k1 = kb ^ ((2 * i + 1) << 5);
            ldsm4(a[i][0], k0); ldsm4(a[i][1], k1); ldsm4(a[i][2], k0 + 4096); ldsm4(a[i][3], k1 + 4096);
            if (i > 0) {
                mma16816(sa0, a[i - 1][0], q[i - 1][0], q[i - 1][1]); mma16816(sa1, a[i - 1][1], q[i - 1][2], q[i - 1][3]);
                mma16816(sb0, a[i - 1][2], q[i - 1][0], q[i - 1][1]); mma16816(sb1, a[i - 1][3], q[i - 1][2], q[i - 1][3]);
            }
        }
        mma16816(sa0, a[3][0], q[3][0], q[3][1]); mma16816(sa1, a[3][1], q[3][2], q[3][3]);
        mma16816(sb0, a[3][2], q[3][0], q[3][1]); mma16816(sb1, a[3][3], q[3][2], q[3][3]);
    }
    const uint32_t vb = tile + voff;
    uint32_t av[8][4];
    pv_load(av, vb);
    const bool refill = ((fill & 7) - 1u) < 2u;
    const uint32_t fbar = bars + ((fill >> 4) & 0x7ff);
    const size_t foff = ((size_t)blockIdx.x << 19) + ((fill >> 16) << 13);
    if (fill & F_NORM) asm("createpolicy.fractional.L2::evict_normal.b64 %0, 1.0;" : "=l"(pol));
    const char* kbase = reinterpret_cast<const char*>(p.k);
    const char* vbase = reinterpret_cast<const char*>(p.v);
    half_fill(refill, true, fill & 2, tile, kbase + foff, fbar, pol, p.zero);
    const bool odd = L.g & 1;
    const bool valid = (L.v == 0);
    const float s0 = (odd ? sa0[1] + sa1[1] : sa0[0] + sa1[0]) * SCL, s1 = (odd ? sa0[3] + sa1[3] : sa0[2] + sa1[2]) * SCL;
    const float s2 = (odd ? sb0[1] + sb1[1] : sb0[0] + sb1[0]) * SCL, s3 = (odd ? sb0[3] + sb1[3] : sb0[2] + sb1[2]) * SCL;
    float mx = valid ? fmaxf(fmaxf(s0, s1), fmaxf(s2, s3)) : -INFINITY;
    if (__any_sync(0xffffffffu, mx > S.m)) {
#pragma unroll
        for (int o = 16; o > 0; o >>= 1) mx = fmaxf(mx, __shfl_xor_sync(0xffffffffu, mx, o));
        const float f = ex2(S.m - mx);
        S.o[0] *= f; S.o[1] *= f; S.o[2] *= f; S.o[3] *= f; S.l *= f;
        S.m = mx;
    }
    const float p0 = ex2(s0 - S.m), p1 = ex2(s1 - S.m), p2 = ex2(s2 - S.m), p3 = ex2(s3 - S.m);
    if (valid) S.l += (p0 + p1) + (p2 + p3);
    const PVB ba = spread(pack_bf16(p0, p1), L), bb = spread(pack_bf16(p2, p3), L);
    float o1[4] = {0.f, 0.f, 0.f, 0.f}, o2[4] = {0.f, 0.f, 0.f, 0.f}, o3[4] = {0.f, 0.f, 0.f, 0.f};
#pragma unroll
    for (int c = 0; c < 8; c += 2) {
        const bool on = (L.v == (c >> 1));
        uint32_t w0[4], w1[4];
        ldsm4t(w0, (vb ^ (c << 4)) + 4096); ldsm4t(w1, (vb ^ ((c + 1) << 4)) + 4096);
        mma16816(S.o, av[c], on ? ba.x0 : 0u, on ? ba.y0 : 0u);
        mma16816(o1, av[c + 1], on ? ba.x1 : 0u, on ? ba.y1 : 0u);
        mma16816(o2, w0, on ? bb.x0 : 0u, on ? bb.y0 : 0u);
        mma16816(o3, w1, on ? bb.x1 : 0u, on ? bb.y1 : 0u);
    }
    half_fill(refill, false, fill & 2, tile + HALF_B, vbase + foff, fbar, pol, p.zero);
    S.o[0] += o1[0] + (o2[0] + o3[0]); S.o[1] += o1[1] + (o2[1] + o3[1]);
    S.o[2] += o1[2] + (o2[2] + o3[2]); S.o[3] += o1[3] + (o2[3] + o3[3]);
}

__device__ __forceinline__ void flush_ctx(Ctx& S, uint32_t part, bool first, int lane, const LaneC& L) {
    float l = S.l;
#pragma unroll
    for (int o = 16; o > 0; o >>= 1) l += __shfl_xor_sync(0xffffffffu, l, o);
    const uint32_t a = part + (16 * L.t + L.g) * 4;
    float m = S.m;
    if (!first) {
        const float mo = ldsf(part + 512), lo = ldsf(part + 516);
        m = fmaxf(mo, S.m);
        const float fo = ex2(mo - m), fn = ex2(S.m - m);
        S.o[0] = S.o[0] * fn + ldsf(a) * fo; S.o[1] = S.o[1] * fn + ldsf(a + 32) * fo;
        S.o[2] = S.o[2] * fn + ldsf(a + 256) * fo; S.o[3] = S.o[3] * fn + ldsf(a + 288) * fo;
        l = l * fn + lo * fo;
        __syncwarp();
    }
    stsf(a, S.o[0]); stsf(a + 32, S.o[1]); stsf(a + 256, S.o[2]); stsf(a + 288, S.o[3]);
    if (lane == 0) { stsf(part + 512, m); stsf(part + 516, l); }
    S.o[0] = S.o[1] = S.o[2] = S.o[3] = 0.f; S.l = 0.f; S.m = -INFINITY;
    __syncwarp();
}

template <bool PF> __device__ __forceinline__ void tma2d(uint32_t dst, const CUtensorMap* map, int c0, int c1, uint32_t bar, uint64_t pol) {
    if (PF) asm volatile("cp.async.bulk.prefetch.tensor.2d.L2.global.tile [%0, {%1, %2}];" ::"l"(map), "r"(c0), "r"(c1) : "memory");
    else asm volatile("cp.async.bulk.tensor.2d.shared::cluster.global.tile.mbarrier::complete_tx::bytes.L2::cache_hint [%0], [%1, {%2, %3}], [%4], %5;"
                      ::"r"(dst), "l"(map), "r"(c0), "r"(c1), "r"(bar), "l"(pol) : "memory");
}
template <int ST, int I, bool PF> __device__ __forceinline__ void load_chunk(const Params& p, uint32_t dst, uint32_t bar, uint64_t pol) {
    const int cta = blockIdx.x;
    if (ST == 0) {
        tma2d<PF>(dst, &p.mwo, 128 * I, 32 * cta, bar, pol); tma2d<PF>(dst + 4096, &p.mwo, 128 * I + 64, 32 * cta, bar, pol);
    } else if (ST == 1 && I < 2) {
        tma2d<PF>(dst, &p.mw1, 16 * cta, 256 * I, bar, pol);
    } else if (ST == 1) {
#pragma unroll
        for (int i = 0; i < 4; i++) tma2d<PF>(dst + i * 2048, &p.mw2, 256 * (I - 2) + 64 * i, 16 * cta, bar, pol);
    } else {
        tma2d<PF>(dst, &p.mwq, 128 * (cta >> 2) + 64 * (I >> 1), 128 * (cta & 3) + 64 * (I & 1), bar, pol);
    }
}
struct WBuf {
    uint32_t a[3], bar, par;
    __device__ __forceinline__ void wait3() { mbar_wait(bar, par); }
    __device__ __forceinline__ void wait4() { mbar_wait(bar + 8, par); }
    __device__ __forceinline__ void rotate() { const uint32_t x = a[0]; a[0] = a[1]; a[1] = a[2]; a[2] = x; par ^= 1; }
};
template <int ST, bool PF4> __device__ __forceinline__ void load_stage1(const Params& p, const WBuf& W, uint64_t pol) {
    if (ST == 1 && blockIdx.x >= NMLP) { mbar_arrive(W.bar); mbar_arrive(W.bar + 8); return; }
    if (ST == 0) asm volatile("fence.proxy.async.shared::cta;" ::: "memory");
    mbar_expect_tx(W.bar, 3 * 8192);
    load_chunk<ST, 0, false>(p, W.a[0], W.bar, pol);
    load_chunk<ST, 1, false>(p, W.a[1], W.bar, pol);
    load_chunk<ST, 2, false>(p, W.a[2], W.bar, pol);
    if (PF4) load_chunk<ST, 3, true>(p, 0, 0, pol);
}
template <int ST, bool PF4> __device__ __forceinline__ void load_stage(const Params& p, const WBuf& W, uint64_t pol) {
    __syncwarp();
    if (elect_one()) load_stage1<ST, PF4>(p, W, pol);
    __syncwarp();
}
template <int ST> __device__ __forceinline__ void load_fourth(const Params& p, const WBuf& W, uint64_t pol) {
    __syncwarp();
    if (ST == 2) {
        int l; asm volatile("mov.u32 %0, %%laneid;" : "=r"(l));
        const char* src = reinterpret_cast<const char*>(p.wq) + (size_t)(128 * (blockIdx.x & 3) + 64 + (l >> 3)) * (HD * 2) + (blockIdx.x >> 2) * 256 + 128 + (l & 7) * 16;
        const uint32_t d0 = W.a[0] ^ (((l >> 3) * 128 + (((l & 7) ^ (l >> 3)) << 4)) | p.zero), d1 = d0 ^ 64;
#pragma unroll
        for (int u = 0; u < 16; u++)
            asm volatile("cp.async.ca.shared.global.L2::cache_hint [%0], [%1], 16, %2;"
                         ::"r"(((u & 1) ? d1 : d0) + u * 512), "l"(src + 4 * u * (HD * 2)), "l"(pol) : "memory");
        asm volatile("cp.async.mbarrier.arrive.shared::cta.b64 [%0];" ::"r"(W.bar + 8) : "memory");
        __syncwarp();
        mbar_arrive_elect(W.bar + 8);
    } else if (elect_one()) { mbar_expect_tx(W.bar + 8, 8192); load_chunk<ST, 3, false>(p, W.a[0], W.bar + 8, pol); }
    __syncwarp();
}
__device__ __forceinline__ void frag8(uint32_t (&f)[8][4], uint32_t a) {
#pragma unroll
    for (int u = 0; u < 4; u++) { ldsm4t(f[u], a ^ (u << 5)); ldsm4t(f[4 + u], (a ^ (u << 5)) + 2048); }
}
template <int N, int STRIDE, int HALF> __device__ __forceinline__ void ll_gather(const uint32_t* src, int n, uint32_t tag, uint32_t (&w)[N][4]) {
#pragma unroll
    for (int i = 0; i < N; i++) w[i][0] = w[i][1] = w[i][2] = w[i][3] = i < n ? 0u : tag;
    uint32_t it = 0;
    while (true) {
#pragma unroll
        for (int i = 0; i < N; i++) ld_w4(src + (HALF ? (i & 3) * STRIDE + (i >> 2) * HALF : i * STRIDE), miss4(w[i], tag), w[i]);
        bool miss = false;
#pragma unroll
        for (int i = 0; i < N; i++) miss |= miss4(w[i], tag);
        if (!__any_sync(0xffffffffu, miss)) break;
        SPIN_GUARD(it);
    }
}
__device__ __forceinline__ void pick4(float (&o)[4], const float (&a0)[4], const float (&a1)[4], const float (&a2)[4], const float (&a3)[4], int t) {
#pragma unroll
    for (int i = 0; i < 4; i++) o[i] = (t & 2) ? ((t & 1) ? a3[i] : a2[i]) : ((t & 1) ? a1[i] : a0[i]);
}
template <bool COLL> __device__ __forceinline__ void issue_fill(uint32_t fill, uint32_t dst, uint32_t bars, const Params& p, uint64_t pol) {
    const uint32_t fbar = bars + ((fill >> 4) & 0x7ff);
    const size_t foff = ((size_t)blockIdx.x << 19) + ((fill >> 16) << 13);
    if (fill & F_NORM) asm("createpolicy.fractional.L2::evict_normal.b64 %0, 1.0;" : "=l"(pol));
    const char* kbase = reinterpret_cast<const char*>(p.k);
    const char* vbase = reinterpret_cast<const char*>(p.v);
    if (COLL) {
        half_fill(true, true, fill & 2, dst, kbase + foff, fbar, pol, p.zero);
        half_fill(true, false, fill & 2, dst + HALF_B, vbase + foff, fbar, pol, p.zero);
    } else {
        mbar_expect_tx(fbar, SLOT_B);
        bulk_g2s(dst, kbase + foff, HALF_B, fbar, pol);
        bulk_g2s(dst + HALF_B, vbase + foff, HALF_B, fbar, pol);
    }
}
__device__ __forceinline__ uint2 lds64(uint32_t a) {
    uint2 r;
    asm volatile("ld.shared.v2.u32 {%0,%1}, [%2];" : "=r"(r.x), "=r"(r.y) : "r"(a) : "memory");
    return r;
}
__device__ __forceinline__ uint2 uniform2(uint2 r) {
    r.x = __shfl_sync(0xffffffffu, r.x, 0); r.y = __shfl_sync(0xffffffffu, r.y, 0);
    return r;
}

__device__ __forceinline__ float gelu_tanh(float x) {
    const float u = 0.7978845608028654f * (x + 0.044715f * x * x * x);
    const float th = 1.f - 2.f / (__expf(2.f * u) + 1.f);
    return 0.5f * x * (1.f + th);
}

template <int NB> __device__ __forceinline__ void gather_o(const uint32_t* src, int lane_off, uint32_t tag, bool live, float (&o)[NB]) {
    uint32_t wm[4 * NB], wl[4 * NB], wo[4 * NB];
#pragma unroll
    for (int i = 0; i < 4 * NB; i++) wm[i] = wl[i] = wo[i] = live ? 0u : tag;
    uint32_t it = 0;
    while (true) {
#pragma unroll
        for (int i = 0; i < 4 * NB; i++) {
            const uint32_t* q = src + (i >> 2) * (NCTA * 160) + (i & 3) * 160;
            ld_w2(q + 128, (((wm[i] ^ tag) | (wl[i] ^ tag)) & 15u) != 0, wm[i], wl[i]);
            ld_w1(q + lane_off, ((wo[i] ^ tag) & 15u) != 0, wo[i]);
        }
        uint32_t miss = 0;
#pragma unroll
        for (int i = 0; i < 4 * NB; i++) miss |= (wm[i] ^ tag) | (wl[i] ^ tag) | (wo[i] ^ tag);
        if (!__any_sync(0xffffffffu, (miss & 15u) != 0)) break;
        SPIN_GUARD(it);
    }
#pragma unroll
    for (int b = 0; b < NB; b++) {
        const float M = fmaxf(fmaxf(ll_val(wm[4 * b]), ll_val(wm[4 * b + 1])), fmaxf(ll_val(wm[4 * b + 2]), ll_val(wm[4 * b + 3])));
        float Ls = 0.f, O = 0.f;
#pragma unroll
        for (int i = 4 * b; i < 4 * b + 4; i++) { const float f = ex2(ll_val(wm[i]) - M); Ls += ll_val(wl[i]) * f; O += ll_val(wo[i]) * f; }
        o[b] = O / Ls;
    }
}
__device__ __forceinline__ void bar256() { asm volatile("bar.sync 1, 256;" ::: "memory"); }
__device__ __forceinline__ void red_sf(uint32_t a, float v) { asm volatile("red.shared.add.f32 [%0], %1;" ::"r"(a), "f"(v) : "memory"); }
__device__ __forceinline__ void fill_ones(uint32_t a, int lane) {
    const uint32_t o[4] = {0x3f803f80u, 0x3f803f80u, 0x3f803f80u, 0x3f803f80u};
    sts128(a + lane * 16, o); sts128(a + 512 + lane * 16, o);
}
__device__ __forceinline__ void ln_store2(const float (&x)[2][16], uint32_t xn, int lane) {
    float s[2] = {0.f, 0.f}, q[2] = {0.f, 0.f};
#pragma unroll
    for (int i = 0; i < 32; i++) s[i >> 4] += x[i >> 4][i & 15];
#pragma unroll
    for (int o = 16; o > 0; o >>= 1) { s[0] += __shfl_xor_sync(0xffffffffu, s[0], o); s[1] += __shfl_xor_sync(0xffffffffu, s[1], o); }
    s[0] *= (1.f / DM); s[1] *= (1.f / DM);
#pragma unroll
    for (int i = 0; i < 32; i++) { const float d = x[i >> 4][i & 15] - s[i >> 4]; q[i >> 4] += d * d; }
#pragma unroll
    for (int o = 16; o > 0; o >>= 1) { q[0] += __shfl_xor_sync(0xffffffffu, q[0], o); q[1] += __shfl_xor_sync(0xffffffffu, q[1], o); }
#pragma unroll
    for (int b = 0; b < 2; b++) {
        const float r = rsqrtf(q[b] * (1.f / DM) + 1e-5f), mean = s[b];
#pragma unroll
        for (int i = 0; i < 4; i++)
            sts64(xn + b * XS + (128 * i + 4 * lane) * 2, pack_bf16((x[b][4 * i] - mean) * r, (x[b][4 * i + 1] - mean) * r),
                  pack_bf16((x[b][4 * i + 2] - mean) * r, (x[b][4 * i + 3] - mean) * r));
    }
}

__global__ void __launch_bounds__(384, 1) fused_kernel(const __grid_constant__ Params p) {
    extern __shared__ __align__(1024) unsigned char smem_raw[];
    const uint32_t sb = (uint32_t)__cvta_generic_to_shared(smem_raw);
    const int tid = threadIdx.x, lane = tid & 31;
    const int warp = __shfl_sync(0xffffffffu, tid >> 5, 0);
    const int cta = blockIdx.x;

    const uint32_t bars = sb + SM_BAR;
    if (tid == 0) TSYNC(0);
    uint64_t pol;
    asm volatile("createpolicy.fractional.L2::evict_first.b64 %0, 1.0;" : "=l"(pol));
    WBuf W;
    W.a[0] = sb + SM_W; W.a[1] = sb + SM_W + 8192; W.a[2] = sb + SM_W + 16384; W.bar = bars + BAR_W * 8; W.par = 0;
    if (warp == 0) {
        if (elect_one()) {
#pragma unroll
            for (int k = 0; k < 3; k++) mbar_init(bars + (BAR_FULL + k) * 8, 1);
            mbar_init(bars + BAR_TAB * 8, 1);
            asm volatile("fence.mbarrier_init.release.cluster;" ::: "memory");
            mbar_expect_tx(bars + BAR_TAB * 8, TAB_BYTES);
            asm volatile("cp.async.bulk.shared::cluster.global.mbarrier::complete_tx::bytes [%0], [%1], %2, [%3];"
                         ::"r"(sb + SM_TAB), "l"(&g_tab), "r"(TAB_BYTES), "r"(bars + BAR_TAB * 8) : "memory");
            issue_fill<false>(INITA0, sb, bars, p, pol);
            issue_fill<false>(INITA1, sb + SLOT_B, bars, p, pol);
            issue_fill<false>(INITA2, sb + 2 * SLOT_B, bars, p, pol);
        }
    } else if (warp == 3) {
#pragma unroll
        for (int i = 0; i < 4; i++) cp16(sb + SM_XN + (i >> 1) * XS + (i & 1) * 512 + lane * 16, p.x + 256 * i + 8 * lane);
        if (lane < 2) cp16(sb + SM_BIAS + lane * 16, p.b2 + 16 * (cta & 31) + 8 * lane);
        else if (lane < 4 && cta < NMLP) cp16(sb + SM_BIAS + lane * 16, p.b1 + 16 * cta + 8 * (lane - 2));
        else if (lane == 4) asm volatile("cp.async.ca.shared.global [%0], [%1], 4;" ::"r"(sb + SM_EPOCH), "l"(&g_epoch) : "memory");
        if (elect_one()) {
            asm volatile("prefetch.tensormap [%0];" ::"l"(&p.mwq) : "memory");
            mbar_init(W.bar, 1); mbar_init(W.bar + 8, 1);
            asm volatile("fence.mbarrier_init.release.cluster;" ::: "memory");
            load_stage1<2, true>(p, W, pol);
        }
    } else if (warp >= 4) {
        if (elect_one()) {
            for (int i = warp - 1; i < NBAR; i += 8) {
                if (i == BAR_TAB || i == BAR_W || i == BAR_W + 1) continue;
                int cnt = 1;
                if ((i >= BAR_CAP && i < BAR_FREE) || (i >= BAR_DUMP && i < BAR_Q)) cnt = 8;
                if (i >= BAR_CTX && i < BAR_TAB) cnt = 6;
                mbar_init(bars + i * 8, cnt);
            }
            asm volatile("fence.mbarrier_init.release.cluster;" ::: "memory");
        }
    }
    static_assert(NBAR <= 256, "set-up mapping");
    __syncthreads();

    if (warp >= 4) {
        asm volatile("setmaxnreg.inc.sync.aligned.u32 %0;" ::"n"(REG_HI));
        const uint32_t mine = sb + (tid - 128) * 16 + ((tid >> 5) - 4) * (2048 - 512);
        uint32_t r[NRF][16];
#pragma unroll
        for (int u = 0; u < NRF; u++)
#pragma unroll
            for (int c = 0; c < 16; c++) r[u][c] = 0;
        int nc = 0, nd = 0, uc = 0, ud = 0;
        unsigned long long cs = CAP0, ds = DUMP0;
        uint32_t it = 0;
        while (nd < 2 * NRF) {
            const bool canD = nd < nc, canC = nc < 2 * NRF && nc < nd + NRF;
            const uint32_t bd = bars + (BAR_FREE + nd) * 8, bc = bars + (BAR_RF + nc) * 8;
            if (!canC) mbar_wait_long(bd);
            if (!canD) mbar_wait_long(bc);
            if (canC && mbar_test_warp(bc, 0)) {
                const uint32_t a = mine + (uint32_t)(cs & 15) * SLOT_B;
                raw_dispatch<0, NRF, true>(r, uc, a);
                __syncwarp();
                mbar_arrive_elect(bc + (BAR_CAP - BAR_RF) * 8);
                nc++; cs >>= 4;
                if (++uc == NRF) { uc = 0; cs = CAP1; }
                it = 0;
            } else if (canD && mbar_test_warp(bd, 0)) {
                const uint32_t a = mine + (uint32_t)(ds & 15) * SLOT_B;
                raw_dispatch<0, NRF, false>(r, ud, a);
                __syncwarp();
                mbar_arrive_elect(bd + (BAR_DUMP - BAR_FREE) * 8);
                nd++; ds >>= 4;
                if (++ud == NRF) { ud = 0; ds = DUMP1; }
                it = 0;
            } else {
                __nanosleep(200);
                if (++it > (1u << 24)) __trap();
            }
        }
        {
            const int sw = __shfl_sync(0xffffffffu, (threadIdx.x >> 5) - 4, 0), g = lane >> 2, t = lane & 3;
            const int vrow = (lane & 7) + 8 * (lane >> 4);
            const uint32_t aoff = vrow * 128 + ((((lane >> 3) & 1) ^ (lane & 7)) << 4);
            const uint32_t wb = sb + SM_W, wbar = bars + BAR_W * 8;
            const bool mlp = cta < NMLP, owner = cta >= 64;
            const int ob = cta >= 96 ? 0 : 1, oo = cta & 31;
            uint32_t fo[8][4], f1[4][4], f2[4][4];
            mbar_wait(wbar, 1);
            if (sw < 6) frag8(fo, wb + (((sw >> 1) + 1) % 3) * 8192 + aoff + (sw & 1) * 4096);
            bar256();
            if (tid == 128) { mbar_expect_tx(wbar, 8192); load_chunk<0, 3, false>(p, wb, wbar, pol); }
            mbar_wait(wbar, 0);
            if (sw >= 6) frag8(fo, wb + aoff + (sw & 1) * 4096);
            bar256();
            const uint32_t my = wb + sw * 1024, redH = wb + 8192, redO = wb + 8192 + 512;
            if (lane < 4) sts32(my + 160 + lane * 4, 0x3f803f80u);
            const uint32_t vb = my + (lane & 1) * 80 + (lane >> 3) * 16;
            const uint32_t xb = (lane & 2) ? my + 160 : my + 256 + (lane & 1) * 144 + (lane >> 3) * 16;
            const uint32_t xs = (lane & 2) ? 0 : 64;
            const uint32_t epoch = lds32(sb + SM_EPOCH);
            const uint32_t tag0 = epoch % 15u + 1u, tagA = ((epoch % 15u) * 6u + 6u) % 15u + 1u, tagB = ((epoch % 15u) * 6u + 7u) % 15u + 1u;
            const float bias = mlp ? bf_lo(lds16(sb + SM_BIAS + 32 + (g + 4 * (t & 2)) * 2)) : 0.f;
            uint32_t* const outbox = &g_inbox[0][4 * sw + t][cta][g];
            constexpr int OB = 32 * NCTA * 16;
            mbar_wait_long(bars + (BAR_PRE + 3) * 8);
#pragma unroll 1
            for (int pass = 0; pass < 2; pass++) {
                const bool live = pass;
                const uint32_t keep = live ? 0xffffffffu : 0u;
                auto send4 = [&](const float (&acc)[4][4], uint32_t tag) {
                    float o[4];
                    pick4(o, acc[0], acc[1], acc[2], acc[3], t);
                    st_w(outbox, ll_pack(o[0], tag) & keep); st_w(outbox + 8, ll_pack(o[2], tag) & keep);
                    st_w(outbox + OB, ll_pack(o[1], tag) & keep); st_w(outbox + OB + 8, ll_pack(o[3], tag) & keep);
                };
                auto own = [&](int st, uint32_t tag) {
                    uint32_t w[2][4];
                    ll_gather<2, 128, 0>(&g_inbox[ob][oo][0][0] + sw * 256 + 4 * lane, (live && !(st && sw == 7)) ? 2 : 0, tag, w);
                    float c[4];
#pragma unroll
                    for (int e = 0; e < 4; e++) {
                        c[e] = ll_val(w[0][e]) + ll_val(w[1][e]);
                        c[e] += __shfl_xor_sync(0xffffffffu, c[e], 4); c[e] += __shfl_xor_sync(0xffffffffu, c[e], 8); c[e] += __shfl_xor_sync(0xffffffffu, c[e], 16);
                    }
                    if (lane < 4) sts128(redO + st * 512 + sw * 64 + lane * 16, reinterpret_cast<const uint32_t*>(c));
                    bar256();
                    if (sw == 0) {
                        uint32_t u[4], v[4];
                        lds128(u, redO + st * 512 + (lane >> 2) * 64 + t * 16);
                        lds128(v, sb + SM_XO + t * 16);
                        const uint32_t b01 = lds32(sb + SM_BIAS + t * 8), b23 = lds32(sb + SM_BIAS + t * 8 + 4);
                        float x[4];
#pragma unroll
                        for (int e = 0; e < 4; e++) {
                            float y = __uint_as_float(u[e]);
                            y += __shfl_xor_sync(0xffffffffu, y, 4); y += __shfl_xor_sync(0xffffffffu, y, 8); y += __shfl_xor_sync(0xffffffffu, y, 16);
                            const float b2 = e == 0 ? bf_lo(b01) : (e == 1 ? bf_hi(b01) : (e == 2 ? bf_lo(b23) : bf_hi(b23)));
                            x[e] = bfr(__uint_as_float(v[e]) + (st == 0 ? bfr(y) : bfr(bfr(y) + b2)));
                        }
                        if (st == 0) {
                            st_w4(&g_xrow[2 + ob][lane >> 2][16 * oo + 4 * t], (__float_as_uint(x[0]) | tag) & keep, (__float_as_uint(x[1]) | tag) & keep,
                                                     (__float_as_uint(x[2]) | tag) & keep, (__float_as_uint(x[3]) | tag) & keep);
                            __syncwarp();
                            if (live && lane < 4) sts128(sb + SM_XO + t * 16, reinterpret_cast<const uint32_t*>(x));
                            __syncwarp();
                        } else if (live && lane < 4) {
                            *reinterpret_cast<uint2*>(p.out + ob * DM + 16 * oo + 4 * lane) = make_uint2(pack_bf16(x[0], x[1]), pack_bf16(x[2], x[3]));
                        }
                    }
                };
                if (sw == 0) { sts32(redH + lane * 4, 0); sts32(redH + 128 + lane * 4, 0); }
                float o[2];
                if (live) {
                    mbar_wait_long(bars + (BAR_CTX + 3) * 8);
                    if (tid == 128 && mlp) {
                        mbar_expect_tx(wbar, 4 * 8192);
                        load_chunk<1, 0, false>(p, sb, wbar, pol); load_chunk<1, 1, false>(p, sb + 8192, wbar, pol);
                        load_chunk<1, 2, false>(p, sb + 16384, wbar, pol); load_chunk<1, 3, false>(p, sb + 24576, wbar, pol);
                    }
                }
                gather_o<2>(g_opart[2][cta & ~3], 32 * (cta & 3) + lane, tag0, live, o);
                if (live && sw == 0) TS(32 + 48 + 1);
                sts16(my + lane * 2, pack_bf16(o[0], 0.f)); sts16(my + 80 + lane * 2, pack_bf16(o[1], 0.f));
                __syncwarp();
                uint32_t bx[4];
                ldsm4(bx, vb);
                float acc[4][4];
#pragma unroll
                for (int u = 0; u < 4; u++) { acc[u][0] = acc[u][1] = acc[u][2] = acc[u][3] = 0.f; mma16816(acc[u], fo[u], bx[0], bx[1]); }
#pragma unroll
                for (int u = 0; u < 4; u++) mma16816(acc[u], fo[4 + u], bx[2], bx[3]);
                send4(acc, tagA);
                if (live && sw == 0) TS(32 + 48 + 2);
                if (owner) own(0, tagA); else bar256();
                if (live && sw == 0) TS(32 + 48 + 3);
                if (mlp) {
                    if (live) mbar_wait(wbar, 1);
#pragma unroll
                    for (int u = 0; u < 4; u++) {
                        ldsm4t(f1[u], sb + sw * 2048 + vrow * 32 + ((((lane >> 3) ^ (lane >> 2)) & 1) << 4) + u * 512);
                        ldsm4t(f2[u], ((sb + 16384 + sw * 2048 + aoff) ^ (u << 5)));
                    }
                    uint32_t w[1][4];
                    ll_gather<1, 0, 0>(g_xrow[2 + (lane >> 4)][cta % 8] + 64 * sw + 4 * (lane & 15), live, tagA, w);
                    if (live && sw == 0) TS(32 + 48 + 8);
                    sts64(my + 256 + (lane >> 4) * 144 + (lane & 15) * 8, __byte_perm(w[0][0], w[0][1], 0x7632), __byte_perm(w[0][2], w[0][3], 0x7632));
                    __syncwarp();
                    uint32_t b0[4], b1[4];
                    ldsm4(b0, xb); ldsm4(b1, xb + xs);
#pragma unroll
                    for (int u = 0; u < 4; u++) acc[u][0] = acc[u][1] = acc[u][2] = acc[u][3] = 0.f;
                    mma16816(acc[0], f1[0], b0[0], b0[1]); mma16816(acc[1], f1[1], b0[2], b0[3]);
                    mma16816(acc[2], f1[2], b1[0], b1[1]); mma16816(acc[3], f1[3], b1[2], b1[3]);
                    const float x0 = ll_val(w[0][0]), x1 = ll_val(w[0][1]), x2 = ll_val(w[0][2]), x3 = ll_val(w[0][3]);
                    float s1 = (x0 + x1) + (x2 + x3), s2 = (x0 * x0 + x1 * x1) + (x2 * x2 + x3 * x3);
#pragma unroll
                    for (int q = 8; q > 0; q >>= 1) { s1 += __shfl_xor_sync(0xffffffffu, s1, q); s2 += __shfl_xor_sync(0xffffffffu, s2, q); }
                    if (!(lane & 15)) { red_sf(redH + 192 + (lane >> 4) * 8, s1); red_sf(redH + 196 + (lane >> 4) * 8, s2); }
                    float h4[4];
#pragma unroll
                    for (int i = 0; i < 4; i++) h4[i] = (acc[0][i] + acc[1][i]) + (acc[2][i] + acc[3][i]);
                    const float ha = (t & 2) ? h4[2] : h4[0], hb = (t & 2) ? h4[3] : h4[1];
                    const int unit = g + 4 * (t & 2);
                    if (t & 1) red_sf(redH + 128 + unit * 4, ha);
                    else { red_sf(redH + unit * 8, ha); red_sf(redH + unit * 8 + 4, hb); }
                    bar256();
                    const float hv = ldsf(redH + unit * 8 + (t & 1) * 4), sw1 = ldsf(redH + 128 + unit * 4);
                    const float mean = ldsf(redH + 192 + (t & 1) * 8) * (1.f / DM);
                    const float rs = rsqrtf(fmaxf(ldsf(redH + 196 + (t & 1) * 8) * (1.f / DM) - mean * mean, 0.f) + 1e-5f);
                    sts16(my + (t & 1) * 80 + unit * 2, pack_bf16(gelu_tanh(bfr(bfr((hv - mean * sw1) * rs) + bias)), 0.f));
                    __syncwarp();
                    ldsm4(bx, vb);
#pragma unroll
                    for (int u = 0; u < 4; u++) { acc[u][0] = acc[u][1] = acc[u][2] = acc[u][3] = 0.f; mma16816(acc[u], f2[u], bx[0], bx[1]); }
                    if (live) send4(acc, tagB);
                    if (live && sw == 0) TS(32 + 48 + 5);
                }
                if (owner) own(1, tagB); else bar256();
                if (live && sw == 0) TS(32 + 48 + 6);
            }
            if (tid == 128) TSYNC(1);
            if (cta == NCTA - 1 && tid == 128) asm volatile("st.relaxed.gpu.global.u32 [%0], %1;" ::"l"(&g_epoch), "r"(epoch + 1) : "memory");
        }
    } else {
        asm volatile("setmaxnreg.dec.sync.aligned.u32 %0;" ::"n"(REG_LO));
        LaneC L;
        L.g = lane >> 2; L.t = lane & 3; L.v = (L.g >> 1) ^ L.t;
        L.src0 = 9 * L.t + 4 * (L.g & 1); L.src1 = 9 * L.t + 4 * ((L.g & 1) ^ 1);
        L.sx0 = (L.g & 1) ? 0x1044u : 0x4410u; L.sy0 = (L.g & 1) ? 0x3244u : 0x4432u;
        L.vrow = (lane & 7) + 8 * (lane >> 4);
        L.voff = ((lane >> 3) & 1) * 128 + ((lane & 7) << 4);

        if (warp < 3) {
            const int w = __shfl_sync(0xffffffffu, threadIdx.x >> 5, 0);
            const uint32_t koff = ((lane & 7) + 8 * ((lane >> 3) & 1)) * 256 + (((lane >> 4) ^ (lane & 7)) << 4);
            const uint32_t voff = HALF_B + L.vrow * 256 + L.voff;
            const int qrow = 4 * (L.g & 3) + L.t;
            const uint32_t qoff = sb + SM_Q + qrow * 64 + (((L.g >> 2) ^ ((qrow >> 1) & 3)) << 4);
            Ctx SA, SB;
            SA.o[0] = SA.o[1] = SA.o[2] = SA.o[3] = 0.f; SA.l = 0.f; SA.m = -INFINITY;
            SB = SA;
            uint32_t pa = sb + SM_TAB + w * LA * 8, pb = sb + SM_TAB + (3 * LA + w * LB) * 8;
            mbar_wait(bars + BAR_TAB * 8, 0);
            uint2 dA = uniform2(lds64(pa)), dB = uniform2(lds64(pb));
            uint32_t flushed = 0, idle = 0;
            auto run = [&](const uint2 d, Ctx& S, int ring) {
                const uint32_t tile = sb + ((d.x >> 16) & 15) * SLOT_B;
                const int ctx = (d.x >> 14) & 3;
                if (!(d.x & D_NOPROC)) process_tile(S, tile, qoff + (ctx & 1) * 1024, koff, voff, L, d.y, bars, p, pol);
                else if (((d.y & 7) - 1u) < 2u) issue_fill<true>(d.y, tile, bars, p, pol);
                if ((d.y & 7) == F_FREE) { __syncwarp(); if (lane == 0) mbar_arrive(bars + ((d.y >> 4) & 0x7ff)); }
                if (d.x & (D_FLUSH | D_PRE)) {
                    if (d.x & D_FLUSH) {
                        flush_ctx(S, sb + SM_PART + ((ctx & 1) * 3 + w) * 528, !((flushed >> ctx) & 1), lane, L);
                        flushed |= 1u << ctx;
                        TS(ring * 12 + ctx * 3 + w);
                    }
                    if (lane == 0) mbar_arrive(bars + (((d.x & D_FLUSH) ? BAR_CTX : BAR_PRE) + ctx) * 8);
                }
            };
            while (true) {
                if (!(dA.x & D_END) && mbar_test_warp(bars + (dA.x & 0x7ff), (dA.x >> 11) & 1)) {
                    pa += 8;
                    const uint2 nx = lds64(pa);
                    run(dA, SA, 0);
                    dA = uniform2(nx);
                    TS(128 + w * LB + ((pa - 8 - sb - SM_TAB) >> 3));
                } else if (!(dB.x & D_END) && mbar_test_warp(bars + (dB.x & 0x7ff), (dB.x >> 11) & 1)) {
                    pb += 8;
                    const uint2 nx = lds64(pb);
                    run(dB, SB, 1);
                    dB = uniform2(nx);
                    TS(128 + w * (LA + LB) + LA + ((pb - 8 - sb - SM_TAB - (3 * LA + w * LB) * 8) >> 3));
                } else {
                    if (dA.x & dB.x & D_END) break;
                    if (++idle > (1u << 25)) __trap();
                    continue;
                }
                idle = 0;
            }
        } else {
            TS(24);
            const int ob = cta >= 96 ? 0 : 1, oo = cta & 31;
            asm volatile("cp.async.wait_all;" ::: "memory");
            __syncwarp();
            const uint32_t epoch = lds32(sb + SM_EPOCH);
            if (lane < 16) stsf(sb + SM_XO + lane * 4, bf_lo(lds16(sb + SM_XN + ob * XS + (16 * oo + lane) * 2)));
            __syncwarp();
            const uint32_t tag0 = epoch % 15u + 1u, ubase = (epoch % 15u) * 6u;
            const uint32_t xnb = sb + SM_XN;
            auto fresh = [&]() { int l = lane; asm volatile("" : "+r"(l)); return l; };
            auto a128 = [&](int l, int k) -> uint32_t { return (((l & 7) + 8 * (l >> 4)) * 128 + ((((l >> 3) & 1) ^ (l & 7)) << 4)) ^ (k << 5); };
            auto a32 = [&](int l, int k) -> uint32_t { return ((l & 7) + 8 * (l >> 4)) * 32 + ((((l >> 3) ^ (l >> 2)) & 1) << 4) + k * 512; };
            auto vb_f = [&]() -> uint32_t { return sb + SM_V + (fresh() >> 3) * 16; };
            auto xb_f = [&]() -> uint32_t { const int l = fresh(); return xnb + (l & 1) * XS + (l >> 3) * 16; };
            auto reset_o = [&](int ctx) {
                int l = lane; asm volatile("" : "+r"(l));
                uint32_t* dst = g_opart[ctx][cta] + l;
#pragma unroll
                for (int i = 0; i < 4; i++) st_w(dst + 32 * i, 0);
                if (lane < 8) st_w(dst + 128, 0);
            };
            auto publish = [&](int ctx) {
                mbar_wait(bars + (BAR_CTX + ctx) * 8, 0);
                const uint32_t pa = sb + SM_PART + (ctx & 1) * 3 * 528;
                const float m0 = ldsf(pa + 512), m1 = ldsf(pa + 528 + 512), m2 = ldsf(pa + 1056 + 512);
                const float Mt = ll_val(__float_as_uint(fmaxf(m0, fmaxf(m1, m2))));
                const float f0 = ex2(m0 - Mt), f1 = ex2(m1 - Mt), f2 = ex2(m2 - Mt);
                int l = lane; asm volatile("" : "+r"(l));
                uint32_t* dst = g_opart[ctx][cta] + l;
#pragma unroll
                for (int i = 0; i < 4; i++) {
                    const uint32_t a = pa + (l + 32 * i) * 4;
                    ll_store(dst + 32 * i, ldsf(a) * f0 + ldsf(a + 528) * f1 + ldsf(a + 1056) * f2, tag0);
                }
                if (lane < 8) ll_store(dst + 128, lane ? ldsf(pa + 516) * f0 + ldsf(pa + 528 + 516) * f1 + ldsf(pa + 1056 + 516) * f2 : Mt, tag0);
            };
#pragma unroll 1
            for (int gi = 0; gi < 5; gi++) {
                const int h = cta >> 2, j = cta & 3, bb = (gi - 1) & 1;
                const bool owner = cta >= 64 && ob == bb;
                auto outbox_p = [&]() { const int l = fresh(); return &g_inbox[bb][l & 3][cta][l >> 2]; };
                auto qout_p = [&]() { const int l = fresh(); return g_qpart[gi ? 2 + bb : 0][cta] + 16 * (l & 3) + (l >> 2); };
                auto xout_p = [&]() { const int l = fresh(); return &g_xrow[ob][l >> 2][16 * oo + 4 * (l & 3)]; };
                if (gi != 3) {
                    if (gi) { mbar_wait_long(bars + (BAR_PRE + gi - 1) * 8); reset_o(gi - 1); }
                    if (gi < 3) {
                        uint32_t* const qout = qout_p();
                        uint32_t* const outbox = outbox_p();
                        st_w(qout, 0); st_w(qout + 8, 0); st_w(qout + 64, 0); st_w(qout + 72, 0);
                        if (gi) {
#pragma unroll
                            for (int i = 0; i < 8; i++) { st_w(outbox + i * 4 * NCTA * 16, 0); st_w(outbox + i * 4 * NCTA * 16 + 8, 0); }
                            if (owner) { uint32_t* xo = xout_p(); st_w4(xo, 0, 0, 0, 0); st_w4(xo + 8192, 0, 0, 0, 0); }
                        } else {
                            st_w(qout + NCTA * 128, 0); st_w(qout + NCTA * 128 + 8, 0); st_w(qout + NCTA * 128 + 64, 0); st_w(qout + NCTA * 128 + 72, 0);
                        }
                    }
                }
                if (gi >= 3) { publish(gi - 1); TS(32 + 48); continue; }
#pragma unroll 1
                for (int st = (gi == 0 ? 2 : 0); st < 3; st++) {
                    const uint32_t tag = (ubase + 2 * gi + st) % 15u + 1u, tagp = (ubase + 2 * gi + st + 14u) % 15u + 1u;
                    uint32_t f[2][8][4];
                    if (gi == 0) {
                        float x[2][16];
#pragma unroll
                        for (int i = 0; i < 8; i++) {
                            uint32_t v[2];
                            asm volatile("ld.shared.v2.u32 {%0,%1}, [%2];" : "=r"(v[0]), "=r"(v[1]) : "r"(xnb + (i >> 2) * XS + (128 * (i & 3) + 4 * lane) * 2) : "memory");
                            float* xx = &x[i >> 2][4 * (i & 3)];
                            xx[0] = bf_lo(v[0]); xx[1] = bf_hi(v[0]); xx[2] = bf_lo(v[1]); xx[3] = bf_hi(v[1]);
                        }
                        ln_store2(x, xnb, lane);
                    }
                    W.wait3();
                    {
                        const int l = fresh();
#pragma unroll
                        for (int k = 0; k < 4; k++) {
                            const uint32_t a = W.a[0] + (st == 1 ? a32(l, k) : a128(l, k));
#pragma unroll
                            for (int u = 0; u < 4; u++) ldsm4t(f[u >> 1][4 * (u & 1) + k], a + u * 2048);
                        }
                    }
                    if (st == 0) load_fourth<0>(p, W, pol);
                    else if (st == 2) load_fourth<2>(p, W, pol);
                    else if (cta < NMLP) load_fourth<1>(p, W, pol);
                    if (st == 0) {
                        publish(bb);
                        TS(32 + gi * 16);
                        float o1[1];
                        gather_o<1>(g_opart[bb][4 * h], 32 * j + fresh(), tag0, true, o1);
                        sts16(sb + SM_V + lane * 2, pack_bf16(o1[0], 0.f));
                        __syncwarp();
                        uint32_t bx[4];
                        ldsm4(bx, vb_f());
                        TS(32 + gi * 16 + 1);
                        {
                            uint32_t* const outbox = outbox_p();
                            uint32_t* d = outbox;
                            const int l = fresh();
#pragma unroll 1
                            for (int c = 0; c < 4; c++) {
                                if (c == 2) W.wait4();
                                const uint32_t nx = (c == 0 ? W.a[1] : (c == 1 ? W.a[2] : W.a[0])) + a128(l, 0);
#pragma unroll
                                for (int hf = 0; hf < 2; hf++) {
                                    float acc[4][4], o[4];
#pragma unroll
                                    for (int u = 0; u < 4; u++) {
                                        acc[u][0] = acc[u][1] = acc[u][2] = acc[u][3] = 0.f;
                                        mma16816(acc[u], f[hf][u], bx[0], bx[1]);
                                    }
#pragma unroll
                                    for (int u = 0; u < 4; u++) mma16816(acc[u], f[hf][4 + u], bx[2], bx[3]);
                                    frag8(f[hf], nx + hf * 4096);
                                    pick4(o, acc[0], acc[1], acc[2], acc[3], l & 3);
                                    ll_store(d, o[0], tag); ll_store(d + 8, o[2], tag);
                                    d += 4 * NCTA * 16;
                                }
                            }
                        }
                        W.rotate();
                        TS(32 + gi * 16 + 2);
                        if (!owner) load_stage<1, false>(p, W, pol);
                    } else {
                        float s1 = 0.f, s2 = 0.f;
                        if (gi && (st == 2 || cta < NMLP)) {
                            uint32_t w[4][4];
                            ll_gather<4, 128, 0>(g_xrow[bb][cta % XR] + 4 * fresh(), 4, tagp, w);
                            TS(32 + gi * 16 + 7 + st);
                            float u[4], v[4];
#pragma unroll
                            for (int i = 0; i < 4; i++) {
                                sts64(xnb + (128 * i + 4 * lane) * 2, __byte_perm(w[i][0], w[i][1], 0x7632), __byte_perm(w[i][2], w[i][3], 0x7632));
                                const float x0 = ll_val(w[i][0]), x1 = ll_val(w[i][1]), x2 = ll_val(w[i][2]), x3 = ll_val(w[i][3]);
                                u[i] = (x0 + x1) + (x2 + x3);
                                v[i] = (x0 * x0 + x1 * x1) + (x2 * x2 + x3 * x3);
                            }
                            s1 = (u[0] + u[1]) + (u[2] + u[3]); s2 = (v[0] + v[1]) + (v[2] + v[3]);
                        }
                        __syncwarp();
                        auto row_stats = [&]() {
#pragma unroll
                            for (int o = 16; o > 0; o >>= 1) { s1 += __shfl_xor_sync(0xffffffffu, s1, o); s2 += __shfl_xor_sync(0xffffffffu, s2, o); }
                            s1 *= (1.f / DM);
                            s2 = rsqrtf(fmaxf(s2 * (1.f / DM) - s1 * s1, 0.f) + 1e-5f);
                        };
                        if (st == 2) {
                            TS(32 + gi * 16 + 10);
                            uint32_t bq[4][4];
                            {
                                const uint32_t xb = xb_f() + 256 * j;
#pragma unroll
                                for (int u = 0; u < 4; u++) ldsm4(bq[u], xb + 64 * u);
                            }
                            row_stats();
                            uint32_t* d = qout_p();
                            const int l = fresh();
#pragma unroll 1
                            for (int ch = 0; ch < 2; ch++) {
                                float acc[4][4], o[4];
#pragma unroll
                                for (int k = 0; k < 4; k++) acc[k][0] = acc[k][1] = acc[k][2] = acc[k][3] = 0.f;
#pragma unroll
                                for (int rh = 0; rh < 2; rh++) {
                                    if (rh == 0 && ch) W.wait4();
                                    const uint32_t nx = rh ? W.a[2] : (ch ? W.a[0] : W.a[1]);
#pragma unroll
                                    for (int u = 0; u < 4; u++) {
#pragma unroll
                                        for (int k = 0; k < 4; k++)
                                            mma16816(acc[k], f[u >> 1][4 * (u & 1) + k], bq[2 * rh + (u >> 1)][2 * (u & 1)], bq[2 * rh + (u >> 1)][2 * (u & 1) + 1]);
#pragma unroll
                                        for (int k = 0; k < 4; k++) ldsm4t(f[u >> 1][4 * (u & 1) + k], nx + a128(l, k) + u * 2048);
                                    }
                                }
                                pick4(o, acc[0], acc[1], acc[2], acc[3], l & 3);
                                if (gi) { ll_store(d, (o[0] - s1 * o[1]) * s2, tag0); ll_store(d + 8, (o[2] - s1 * o[3]) * s2, tag0); }
                                else {
                                    ll_store(d, o[0], tag0); ll_store(d + 8, o[2], tag0);
                                    ll_store(d + NCTA * 128, o[1], tag0); ll_store(d + NCTA * 128 + 8, o[3], tag0);
                                }
                                d += 64;
                            }
                            W.rotate();
                            TS(32 + gi * 16 + 11);
                            break;
                        }
                        TS(32 + gi * 16 + 12);
                        if (cta < NMLP) {
                            float hh[4][4];
#pragma unroll
                            for (int u = 0; u < 4; u++) hh[u][0] = hh[u][1] = hh[u][2] = hh[u][3] = 0.f;
                            const uint32_t xb = xb_f();
                            const int l = fresh();
#pragma unroll 1
                            for (int c = 0; c < 2; c++) {
                                uint32_t na[4];
#pragma unroll
                                for (int k = 0; k < 4; k++) na[k] = c == 0 ? W.a[1] + a32(l, k) : W.a[2] + a128(l, k);
#pragma unroll
                                for (int s = 0; s < 4; s++) {
                                    uint32_t b0[4], b1[4];
                                    ldsm4(b0, xb + 512 * c + 128 * s); ldsm4(b1, xb + 512 * c + 128 * s + 64);
                                    mma16816(hh[0], f[s >> 1][4 * (s & 1)], b0[0], b0[1]); mma16816(hh[1], f[s >> 1][4 * (s & 1) + 1], b0[2], b0[3]);
                                    mma16816(hh[2], f[s >> 1][4 * (s & 1) + 2], b1[0], b1[1]); mma16816(hh[3], f[s >> 1][4 * (s & 1) + 3], b1[2], b1[3]);
#pragma unroll
                                    for (int k = 0; k < 4; k++) ldsm4t(f[s >> 1][4 * (s & 1) + k], na[k] + s * 2048);
                                }
                                if (c == 0) row_stats();
                            }
                            float hs4[4];
#pragma unroll
                            for (int i = 0; i < 4; i++) hs4[i] = (hh[0][i] + hh[1][i]) + (hh[2][i] + hh[3][i]);
                            const float hv = (((l & 2) ? hs4[2] : hs4[0]) - s1 * ((l & 2) ? hs4[3] : hs4[1])) * s2;
                            const float bias = bf_lo(lds16(sb + SM_BIAS + 32 + ((l >> 2) + 4 * (l & 2)) * 2));
                            uint32_t* const outbox = outbox_p();
                            sts16(sb + SM_V + ((l >> 2) + 4 * (l & 2)) * 2, pack_bf16(gelu_tanh(bfr(bfr(hv) + bias)), 0.f));
                            __syncwarp();
                            uint32_t bx[4];
                            ldsm4(bx, vb_f());
                            W.wait4();
                            uint32_t* d = outbox;
#pragma unroll 1
                            for (int c = 0; c < 2; c++) {
#pragma unroll
                                for (int s = 0; s < 4; s++) {
                                    float acc[4][4], o[4];
#pragma unroll
                                    for (int u = 0; u < 4; u++) {
                                        acc[u][0] = acc[u][1] = acc[u][2] = acc[u][3] = 0.f;
                                        mma16816(acc[u], f[s >> 1][4 * (s & 1) + u], bx[0], bx[1]);
                                    }
#pragma unroll
                                    for (int u = 0; u < 4; u++) ldsm4t(f[s >> 1][4 * (s & 1) + u], W.a[0] + a128(l, u) + s * 2048);
                                    pick4(o, acc[0], acc[1], acc[2], acc[3], l & 3);
                                    ll_store(d, o[0], tag); ll_store(d + 8, o[2], tag);
                                    d += 4 * NCTA * 16;
                                }
                            }
                        }
                        W.rotate();
                        TS(32 + gi * 16 + 5);
                        if (!owner) load_stage<2, false>(p, W, pol);
                    }
                    if (owner) {
                        uint32_t w[16][4];
                        ll_gather<16, 128, 0>(&g_inbox[ob][oo][0][0] + 4 * fresh(), st == 0 ? 16 : NMLP / 8, tag, w);
                        float xown[4];
                        lds128(reinterpret_cast<uint32_t*>(xown), sb + SM_XO + (lane & 3) * 16);
                        const uint32_t b01 = lds32(sb + SM_BIAS + (lane & 3) * 8), b23 = lds32(sb + SM_BIAS + (lane & 3) * 8 + 4);
                        const float b2own[4] = {bf_lo(b01), bf_hi(b01), bf_lo(b23), bf_hi(b23)};
#pragma unroll
                        for (int e = 0; e < 4; e++) {
                            float c[4];
#pragma unroll
                            for (int i = 0; i < 4; i++) c[i] = (ll_val(w[i][e]) + ll_val(w[4 + i][e])) + (ll_val(w[8 + i][e]) + ll_val(w[12 + i][e]));
                            float t = (c[0] + c[1]) + (c[2] + c[3]);
                            t += __shfl_xor_sync(0xffffffffu, t, 4); t += __shfl_xor_sync(0xffffffffu, t, 8); t += __shfl_xor_sync(0xffffffffu, t, 16);
                            xown[e] = bfr(xown[e] + (st == 0 ? bfr(t) : bfr(bfr(t) + b2own[e])));
                        }
                        { uint32_t* xo = xout_p(); st_w4(xo, __float_as_uint(xown[0]) | tag, __float_as_uint(xown[1]) | tag, __float_as_uint(xown[2]) | tag, __float_as_uint(xown[3]) | tag);
                        st_w4(xo + 8192, __float_as_uint(xown[0]) | tag, __float_as_uint(xown[1]) | tag, __float_as_uint(xown[2]) | tag, __float_as_uint(xown[3]) | tag); }
                        __syncwarp();
                        if (lane < 4) sts128(sb + SM_XO + lane * 16, reinterpret_cast<const uint32_t*>(xown));
                        TS(32 + gi * 16 + 3 + 3 * st);
                        if (st == 0) load_stage<1, false>(p, W, pol); else load_stage<2, false>(p, W, pol);
                    }
                }
                {
                    uint32_t w[8][4];
                    ll_gather<8, 128, NCTA * 128>(g_qpart[gi ? 2 + bb : 0][4 * h] + 4 * fresh(), gi ? 4 : 8, tag0, w);
#pragma unroll
                    for (int bi = 0; bi < 2; bi++) {
                        if (bi == 0 || gi == 0) {
                            float q[4];
#pragma unroll
                            for (int e = 0; e < 4; e++) q[e] = (ll_val(w[4 * bi][e]) + ll_val(w[4 * bi + 1][e])) + (ll_val(w[4 * bi + 2][e]) + ll_val(w[4 * bi + 3][e]));
                            const uint32_t w0 = pack_bf16(q[0], q[1]), w1 = pack_bf16(q[2], q[3]);
                            const int ch = lane >> 1;
#pragma unroll
                            for (int kp = 0; kp < 4; kp++) {
                                const int jj = ch ^ kp;
#pragma unroll
                                for (int e = 0; e < 2; e++) {
                                    const int row = 4 * kp + 2 * (lane & 1) + e;
                                    sts32(sb + SM_Q + (gi ? bb : bi) * 1024 + row * 64 + (((jj >> 2) ^ ((row >> 1) & 3)) << 4) + (jj & 3) * 4, e ? w1 : w0);
                                }
                            }
                        }
                    }
                    __syncwarp();
                    if (lane < (gi ? 1 : 2)) mbar_arrive(bars + (BAR_Q + (gi ? 2 + bb : lane)) * 8);
                }
                TS(32 + gi * 16 + 7);
                load_stage<0, false>(p, W, pol);
                if (gi == 0) fill_ones(xnb + XS, lane);
            }
        }
    }
}

typedef CUresult (*EncodeFn)(CUtensorMap*, CUtensorMapDataType, cuuint32_t, void*, const cuuint64_t*, const cuuint64_t*, const cuuint32_t*,
                             const cuuint32_t*, CUtensorMapInterleave, CUtensorMapSwizzle, CUtensorMapL2promotion, CUtensorMapFloatOOBfill);
void encode2d(EncodeFn fn, CUtensorMap* m, void* base, uint64_t cols, uint64_t rows, uint32_t bcols, uint32_t brows, CUtensorMapSwizzle sw) {
    const cuuint64_t dim[2] = {cols, rows}, stride[1] = {cols * 2};
    const cuuint32_t box[2] = {bcols, brows}, es[2] = {1, 1};
    fn(m, CU_TENSOR_MAP_DATA_TYPE_BFLOAT16, 2, base, dim, stride, box, es, CU_TENSOR_MAP_INTERLEAVE_NONE, sw,
       CU_TENSOR_MAP_L2_PROMOTION_L2_128B, CU_TENSOR_MAP_FLOAT_OOB_FILL_NONE);
}

}

extern "C" void kernel_launch(void* const* d_in, const int* in_sizes, int n_in, void* d_out, int out_size) {
    (void)in_sizes; (void)n_in; (void)out_size;
    static EncodeFn enc = nullptr;
    if (!enc) {
        cudaFuncSetAttribute(fused_kernel, cudaFuncAttributeMaxDynamicSharedMemorySize, (int)SM_TOTAL);
        void* fn = nullptr;
        cudaDriverEntryPointQueryResult qr;
        cudaGetDriverEntryPoint("cuTensorMapEncodeTiled", &fn, cudaEnableDefault, &qr);
        enc = (EncodeFn)fn;
        if (!enc) return;
    }
    Params p;
    encode2d(enc, &p.mwq, d_in[3], HD, DM, 64, 64, CU_TENSOR_MAP_SWIZZLE_128B);
    encode2d(enc, &p.mwo, d_in[4], DM, HD, 64, 32, CU_TENSOR_MAP_SWIZZLE_128B);
    encode2d(enc, &p.mw1, d_in[6], FF, DM, 16, 256, CU_TENSOR_MAP_SWIZZLE_32B);
    encode2d(enc, &p.mw2, d_in[8], DM, FF, 64, 16, CU_TENSOR_MAP_SWIZZLE_128B);
    p.x = (const __nv_bfloat16*)d_in[0];
    p.k = (const __nv_bfloat16*)d_in[1];
    p.v = (const __nv_bfloat16*)d_in[2];
    p.b1 = (const __nv_bfloat16*)d_in[7];
    p.b2 = (const __nv_bfloat16*)d_in[9];
    p.out = (__nv_bfloat16*)d_out;
    p.zero = 0;
    p.wq = (const __nv_bfloat16*)d_in[3];
    fused_kernel<<<NCTA, 384, SM_TOTAL>>>(p);
}
```
